```python
import torch

def _softmax(x, axis=-1):
    return torch.softmax(x, dim=axis)
def _gelu(x):
    return torch.nn.functional.gelu(x, approximate="tanh")
def _silu(x):
    return torch.nn.functional.silu(x)
def _sigmoid(x):
    return torch.sigmoid(x)
def _layernorm(x, axis=-1, eps=1e-5):
    m = x.mean(dim=axis, keepdim=True)
    v = x.var(dim=axis, keepdim=True, unbiased=False)
    return (x - m) / torch.sqrt(v + eps)
def _scatter_add(tgt, idx, src, axis=0):
    return tgt.clone().index_add_(axis, idx, src)
def _segment_sum(src, seg, n):
    out = torch.zeros((n,) + src.shape[1:], dtype=src.dtype)
    return out.index_add_(0, seg, src)
def _pad(x, pw):
    flat = tuple(v for pair in reversed(pw) for v in pair)
    return torch.nn.functional.pad(x, flat)

kernel_name = 'gated_mix__spectral_gfnet__glu_gated_reglu__prompt'

def setup_inputs():

    _w = (lambda a: (lambda t: t.to(torch.bfloat16) if t.is_floating_point() else t)(torch.as_tensor(a)))
    def _A_setup():
        B, S, D = 1, 2048, 640
        Df = D // 2 + 1
        return {
            "x": _w((lambda *s: torch.randn(*s, dtype=torch.bfloat16) * 0.05)(B, S, D)),
            "w_r": _w((lambda *s: torch.randn(*s, dtype=torch.bfloat16) * 0.05)(S, Df) * 0.02),
            "w_i": _w((lambda *s: torch.randn(*s, dtype=torch.bfloat16) * 0.05)(S, Df) * 0.02),
        }
    _A_in = _A_setup()

    def _B_setup():
        B, S, D, F = 1, 2048, 640, 1728
        return {
            "x": _w((lambda *s: torch.randn(*s, dtype=torch.bfloat16) * 0.05)(B, S, D)),
            "W_gate": _w((lambda *s: torch.randn(*s, dtype=torch.bfloat16) * 0.2)(D, F) * (2.0 / D) ** 0.5),
            "W_up": _w((lambda *s: torch.randn(*s, dtype=torch.bfloat16) * 0.2)(D, F) * (2.0 / D) ** 0.5),
            "W_down": _w((lambda *s: torch.randn(*s, dtype=torch.bfloat16) * 0.2)(F, D) * (1.0 / F) ** 0.5),
        }
    _B_in = _B_setup()

    return {
        "A_x": _A_in["x"],
        "A_w_r": _A_in["w_r"],
        "A_w_i": _A_in["w_i"],
        "B_x": _B_in["x"],
        "B_W_gate": _B_in["W_gate"],
        "B_W_up": _B_in["W_up"],
        "B_W_down": _B_in["W_down"],
        "gate_w": _w((lambda *s: torch.randn(*s, dtype=torch.bfloat16) * 0.05)(640) * 16.0),
    }

def reference(A_x, A_w_r, A_w_i, B_x, B_W_gate, B_W_up, B_W_down, gate_w):
    def _A_ref(x, w_r, w_i):
        B, S, D = x.shape
        X = (lambda x, axes=(-2,-1): torch.fft.rfft2(x.float(), dim=axes))(x, axes=(-2, -1))
        W = w_r + 1j * w_i
        X = X * W
        y = (lambda x, s, axes=(-2,-1): torch.fft.irfft2(x, s=s, dim=axes).to(torch.bfloat16))(X, (S, D), axes=(-2, -1))
        return y

    def _B_ref(x, W_gate, W_up, W_down):
        gate = torch.einsum("bsd,df->bsf", x, W_gate)
        up = torch.einsum("bsd,df->bsf", x, W_up)
        gate = gate * (lambda x, dt: x.to(dt))(gate > 0, gate.dtype)
        h = gate * up
        return torch.einsum("bsf,fd->bsd", h, W_down)

    x = A_x
    g = _sigmoid((x * gate_w).sum(-1, keepdims=True))
    a = _A_ref(x, A_w_r, A_w_i)
    b = _B_ref(x, B_W_gate, B_W_up, B_W_down)
    return g * a + (1 - g) * b
```

```cpp
#include <cuda_runtime.h>
#include <cuda_bf16.h>
#include <cuda.h>
#include <stdint.h>
template<int TB> __device__ __forceinline__ void wgmma_rs_n16(float (&d)[8], uint32_t a0, uint32_t a1, uint32_t a2, uint32_t a3, uint64_t db, int scale_d) {
  asm volatile("{\n.reg .pred p;\nsetp.ne.b32 p, %13, 0;\n"
    "wgmma.mma_async.sync.aligned.m64n16k16.f32.bf16.bf16 "
    "{%0, %1, %2, %3, %4, %5, %6, %7}, "
    "{%8, %9, %10, %11}, %12, p, 1, 1, %14;\n}\n"
    : "+f"(d[0]), "+f"(d[1]), "+f"(d[2]), "+f"(d[3]), "+f"(d[4]), "+f"(d[5]), "+f"(d[6]), "+f"(d[7])
    : "r"(a0), "r"(a1), "r"(a2), "r"(a3), "l"(db), "r"(scale_d), "n"(TB));
}
template<int TB> __device__ __forceinline__ void wgmma_rs_n32(float (&d)[16], uint32_t a0, uint32_t a1, uint32_t a2, uint32_t a3, uint64_t db, int scale_d) {
  asm volatile("{\n.reg .pred p;\nsetp.ne.b32 p, %21, 0;\n"
    "wgmma.mma_async.sync.aligned.m64n32k16.f32.bf16.bf16 "
    "{%0, %1, %2, %3, %4, %5, %6, %7, %8, %9, %10, %11, %12, %13, %14, %15}, "
    "{%16, %17, %18, %19}, %20, p, 1, 1, %22;\n}\n"
    : "+f"(d[0]), "+f"(d[1]), "+f"(d[2]), "+f"(d[3]), "+f"(d[4]), "+f"(d[5]), "+f"(d[6]), "+f"(d[7]), "+f"(d[8]), "+f"(d[9]), "+f"(d[10]), "+f"(d[11]), "+f"(d[12]), "+f"(d[13]), "+f"(d[14]), "+f"(d[15])
    : "r"(a0), "r"(a1), "r"(a2), "r"(a3), "l"(db), "r"(scale_d), "n"(TB));
}
template<int TB> __device__ __forceinline__ void wgmma_rs_n64(float (&d)[32], uint32_t a0, uint32_t a1, uint32_t a2, uint32_t a3, uint64_t db, int scale_d) {
  asm volatile("{\n.reg .pred p;\nsetp.ne.b32 p, %37, 0;\n"
    "wgmma.mma_async.sync.aligned.m64n64k16.f32.bf16.bf16 "
    "{%0, %1, %2, %3, %4, %5, %6, %7, %8, %9, %10, %11, %12, %13, %14, %15, %16, %17, %18, %19, %20, %21, %22, %23, %24, %25, %26, %27, %28, %29, %30, %31}, "
    "{%32, %33, %34, %35}, %36, p, 1, 1, %38;\n}\n"
    : "+f"(d[0]), "+f"(d[1]), "+f"(d[2]), "+f"(d[3]), "+f"(d[4]), "+f"(d[5]), "+f"(d[6]), "+f"(d[7]), "+f"(d[8]), "+f"(d[9]), "+f"(d[10]), "+f"(d[11]), "+f"(d[12]), "+f"(d[13]), "+f"(d[14]), "+f"(d[15]), "+f"(d[16]), "+f"(d[17]), "+f"(d[18]), "+f"(d[19]), "+f"(d[20]), "+f"(d[21]), "+f"(d[22]), "+f"(d[23]), "+f"(d[24]), "+f"(d[25]), "+f"(d[26]), "+f"(d[27]), "+f"(d[28]), "+f"(d[29]), "+f"(d[30]), "+f"(d[31])
    : "r"(a0), "r"(a1), "r"(a2), "r"(a3), "l"(db), "r"(scale_d), "n"(TB));
}
template<int TA, int TB> __device__ __forceinline__ void wgmma_ss_n80(float (&d)[40], uint64_t da, uint64_t db, int scale_d) {
  asm volatile("{\n.reg .pred p;\nsetp.ne.b32 p, %42, 0;\n"
    "wgmma.mma_async.sync.aligned.m64n80k16.f32.bf16.bf16 "
    "{%0, %1, %2, %3, %4, %5, %6, %7, %8, %9, %10, %11, %12, %13, %14, %15, %16, %17, %18, %19, %20, %21, %22, %23, %24, %25, %26, %27, %28, %29, %30, %31, %32, %33, %34, %35, %36, %37, %38, %39}, "
    "%40, %41, p, 1, 1, %43, %44;\n}\n"
    : "+f"(d[0]), "+f"(d[1]), "+f"(d[2]), "+f"(d[3]), "+f"(d[4]), "+f"(d[5]), "+f"(d[6]), "+f"(d[7]), "+f"(d[8]), "+f"(d[9]), "+f"(d[10]), "+f"(d[11]), "+f"(d[12]), "+f"(d[13]), "+f"(d[14]), "+f"(d[15]), "+f"(d[16]), "+f"(d[17]), "+f"(d[18]), "+f"(d[19]), "+f"(d[20]), "+f"(d[21]), "+f"(d[22]), "+f"(d[23]), "+f"(d[24]), "+f"(d[25]), "+f"(d[26]), "+f"(d[27]), "+f"(d[28]), "+f"(d[29]), "+f"(d[30]), "+f"(d[31]), "+f"(d[32]), "+f"(d[33]), "+f"(d[34]), "+f"(d[35]), "+f"(d[36]), "+f"(d[37]), "+f"(d[38]), "+f"(d[39])
    : "l"(da), "l"(db), "r"(scale_d), "n"(TA), "n"(TB));
}
template<int TB> __device__ __forceinline__ void wgmma_rs_n80(float (&d)[40], uint32_t a0, uint32_t a1, uint32_t a2, uint32_t a3, uint64_t db, int scale_d) {
  asm volatile("{\n.reg .pred p;\nsetp.ne.b32 p, %45, 0;\n"
    "wgmma.mma_async.sync.aligned.m64n80k16.f32.bf16.bf16 "
    "{%0, %1, %2, %3, %4, %5, %6, %7, %8, %9, %10, %11, %12, %13, %14, %15, %16, %17, %18, %19, %20, %21, %22, %23, %24, %25, %26, %27, %28, %29, %30, %31, %32, %33, %34, %35, %36, %37, %38, %39}, "
    "{%40, %41, %42, %43}, %44, p, 1, 1, %46;\n}\n"
    : "+f"(d[0]), "+f"(d[1]), "+f"(d[2]), "+f"(d[3]), "+f"(d[4]), "+f"(d[5]), "+f"(d[6]), "+f"(d[7]), "+f"(d[8]), "+f"(d[9]), "+f"(d[10]), "+f"(d[11]), "+f"(d[12]), "+f"(d[13]), "+f"(d[14]), "+f"(d[15]), "+f"(d[16]), "+f"(d[17]), "+f"(d[18]), "+f"(d[19]), "+f"(d[20]), "+f"(d[21]), "+f"(d[22]), "+f"(d[23]), "+f"(d[24]), "+f"(d[25]), "+f"(d[26]), "+f"(d[27]), "+f"(d[28]), "+f"(d[29]), "+f"(d[30]), "+f"(d[31]), "+f"(d[32]), "+f"(d[33]), "+f"(d[34]), "+f"(d[35]), "+f"(d[36]), "+f"(d[37]), "+f"(d[38]), "+f"(d[39])
    : "r"(a0), "r"(a1), "r"(a2), "r"(a3), "l"(db), "r"(scale_d), "n"(TB));
}
template<int TA, int TB> __device__ __forceinline__ void wgmma_ss_n128(float (&d)[64], uint64_t da, uint64_t db, int scale_d) {
  asm volatile("{\n.reg .pred p;\nsetp.ne.b32 p, %66, 0;\n"
    "wgmma.mma_async.sync.aligned.m64n128k16.f32.bf16.bf16 "
    "{%0, %1, %2, %3, %4, %5, %6, %7, %8, %9, %10, %11, %12, %13, %14, %15, %16, %17, %18, %19, %20, %21, %22, %23, %24, %25, %26, %27, %28, %29, %30, %31, %32, %33, %34, %35, %36, %37, %38, %39, %40, %41, %42, %43, %44, %45, %46, %47, %48, %49, %50, %51, %52, %53, %54, %55, %56, %57, %58, %59, %60, %61, %62, %63}, "
    "%64, %65, p, 1, 1, %67, %68;\n}\n"
    : "+f"(d[0]), "+f"(d[1]), "+f"(d[2]), "+f"(d[3]), "+f"(d[4]), "+f"(d[5]), "+f"(d[6]), "+f"(d[7]), "+f"(d[8]), "+f"(d[9]), "+f"(d[10]), "+f"(d[11]), "+f"(d[12]), "+f"(d[13]), "+f"(d[14]), "+f"(d[15]), "+f"(d[16]), "+f"(d[17]), "+f"(d[18]), "+f"(d[19]), "+f"(d[20]), "+f"(d[21]), "+f"(d[22]), "+f"(d[23]), "+f"(d[24]), "+f"(d[25]), "+f"(d[26]), "+f"(d[27]), "+f"(d[28]), "+f"(d[29]), "+f"(d[30]), "+f"(d[31]), "+f"(d[32]), "+f"(d[33]), "+f"(d[34]), "+f"(d[35]), "+f"(d[36]), "+f"(d[37]), "+f"(d[38]), "+f"(d[39]), "+f"(d[40]), "+f"(d[41]), "+f"(d[42]), "+f"(d[43]), "+f"(d[44]), "+f"(d[45]), "+f"(d[46]), "+f"(d[47]), "+f"(d[48]), "+f"(d[49]), "+f"(d[50]), "+f"(d[51]), "+f"(d[52]), "+f"(d[53]), "+f"(d[54]), "+f"(d[55]), "+f"(d[56]), "+f"(d[57]), "+f"(d[58]), "+f"(d[59]), "+f"(d[60]), "+f"(d[61]), "+f"(d[62]), "+f"(d[63])
    : "l"(da), "l"(db), "r"(scale_d), "n"(TA), "n"(TB));
}

__device__ __forceinline__ uint32_t smem_u32(const void* p){ return (uint32_t)__cvta_generic_to_shared(p);}
__device__ __forceinline__ void mbar_init(uint32_t a, int c){ asm volatile("mbarrier.init.shared::cta.b64 [%0], %1;"::"r"(a),"r"(c):"memory"); }
__device__ __forceinline__ void mbar_expect_tx(uint32_t a, int bytes){ asm volatile("mbarrier.arrive.expect_tx.shared::cta.b64 _, [%0], %1;"::"r"(a),"r"(bytes):"memory"); }
__device__ __forceinline__ void mbar_arrive(uint32_t a){ asm volatile("mbarrier.arrive.shared::cta.b64 _, [%0];"::"r"(a):"memory"); }
__device__ __forceinline__ void mbar_arrive_if(uint32_t a, uint32_t pred){ asm volatile("{\n.reg .pred p;\nsetp.ne.u32 p, %1, 0;\n@p mbarrier.arrive.shared::cta.b64 _, [%0];\n}"::"r"(a),"r"(pred):"memory"); }
__device__ __forceinline__ bool mbar_try(uint32_t a, int parity){ uint32_t ok; asm volatile("{\n.reg .pred p;\nmbarrier.try_wait.parity.shared::cta.b64 p, [%1], %2;\nselp.u32 %0,1,0,p;\n}":"=r"(ok):"r"(a),"r"(parity):"memory"); return ok;}
#define TIMEOUT(code,val) __trap()
#define MARK(i) do{}while(0)
__device__ __forceinline__ void mbar_wait(uint32_t a, int parity){
  if(mbar_try(a,parity)) return;
  uint32_t it=0;
  while(!mbar_try(a,parity)){ if(++it>(1u<<18)) TIMEOUT((int)(a&0x3ff), parity); }
}
__device__ __forceinline__ bool elect_one(){ uint32_t p; asm volatile("{\n.reg .pred P;\nelect.sync _|P, 0xffffffff;\nselp.u32 %0,1,0,P;\n}":"=r"(p)); return p; }
__device__ __forceinline__ void bulk_load(uint32_t dst, const void* src, int bytes, uint32_t bar){
  asm volatile("cp.async.bulk.shared::cluster.global.mbarrier::complete_tx::bytes [%0], [%1], %2, [%3];"::"r"(dst),"l"(src),"r"(bytes),"r"(bar):"memory");
}
__device__ __forceinline__ void bulk_store(void* dst, uint32_t src, int bytes){
  asm volatile("cp.async.bulk.global.shared::cta.bulk_group [%0], [%1], %2;"::"l"(dst),"r"(src),"r"(bytes):"memory");
}
__device__ __forceinline__ void tma_load_2d(uint32_t dst, const CUtensorMap* tm, int c0, int c1, uint32_t bar){
  asm volatile("cp.async.bulk.tensor.2d.shared::cluster.global.mbarrier::complete_tx::bytes [%0], [%1, {%3,%4}], [%2];"::"r"(dst),"l"(tm),"r"(bar),"r"(c0),"r"(c1):"memory");
}
__device__ __forceinline__ void tma_load_3d(uint32_t dst, const CUtensorMap* tm, int c0, int c1, int c2, uint32_t bar){
  asm volatile("cp.async.bulk.tensor.3d.shared::cluster.global.mbarrier::complete_tx::bytes [%0], [%1, {%3,%4,%5}], [%2];"::"r"(dst),"l"(tm),"r"(bar),"r"(c0),"r"(c1),"r"(c2):"memory");
}
__device__ __forceinline__ void tma_load_4d(uint32_t dst, const CUtensorMap* tm, int c0, int c1, int c2, int c3, uint32_t bar){
  asm volatile("cp.async.bulk.tensor.4d.shared::cluster.global.mbarrier::complete_tx::bytes [%0], [%1, {%3,%4,%5,%6}], [%2];"::"r"(dst),"l"(tm),"r"(bar),"r"(c0),"r"(c1),"r"(c2),"r"(c3):"memory");
}
__device__ __forceinline__ void tma_store_3d(const CUtensorMap* tm, uint32_t src, int c0, int c1, int c2){
  asm volatile("cp.async.bulk.tensor.3d.global.shared::cta.bulk_group [%0, {%2,%3,%4}], [%1];"::"l"(tm),"r"(src),"r"(c0),"r"(c1),"r"(c2):"memory");
}
__device__ __forceinline__ void tma_store_4d(const CUtensorMap* tm, uint32_t src, int c0, int c1, int c2, int c3){
  asm volatile("cp.async.bulk.tensor.4d.global.shared::cta.bulk_group [%0, {%2,%3,%4,%5}], [%1];"::"l"(tm),"r"(src),"r"(c0),"r"(c1),"r"(c2),"r"(c3):"memory");
}
__device__ __forceinline__ void prefetch_l2(const void* p, int bytes){ asm volatile("cp.async.bulk.prefetch.L2.global [%0], %1;"::"l"(p),"r"(bytes):"memory"); }
__device__ __forceinline__ void prefetch_tensor_2d(const CUtensorMap* tm, int c0, int c1){
  asm volatile("cp.async.bulk.prefetch.tensor.2d.L2.global.tile [%0, {%1,%2}];"::"l"(tm),"r"(c0),"r"(c1):"memory");
}
__device__ __forceinline__ void cp_async_arrive_noinc(uint32_t bar){ asm volatile("cp.async.mbarrier.arrive.noinc.shared::cta.b64 [%0];"::"r"(bar):"memory"); }
__device__ __forceinline__ void stg32(void* p, uint32_t v){ asm volatile("st.global.b32 [%0], %1;"::"l"(p),"r"(v):"memory"); }
__device__ __forceinline__ void bulk_commit(){ asm volatile("cp.async.bulk.commit_group;":::"memory"); }
template<int N> __device__ __forceinline__ void bulk_wait(){ asm volatile("cp.async.bulk.wait_group %0;"::"n"(N):"memory"); }
template<int N> __device__ __forceinline__ void bulk_wait_read(){ asm volatile("cp.async.bulk.wait_group.read %0;"::"n"(N):"memory"); }
__device__ __forceinline__ void fence_async_smem(){ asm volatile("fence.proxy.async.shared::cta;":::"memory"); }
__device__ __forceinline__ void fence_async_global(){ asm volatile("fence.proxy.async.global;":::"memory"); }
__device__ __forceinline__ void cp_async16(uint32_t dst, const void* src){ asm volatile("cp.async.cg.shared.global [%0], [%1], 16;"::"r"(dst),"l"(src):"memory"); }
__device__ __forceinline__ void cp_async_commit(){ asm volatile("cp.async.commit_group;":::"memory"); }
template<int N> __device__ __forceinline__ void cp_async_wait(){ asm volatile("cp.async.wait_group %0;"::"n"(N):"memory"); }
__device__ __forceinline__ void named_bar(int id, int n){ asm volatile("bar.sync %0, %1;"::"r"(id),"r"(n):"memory"); }
__device__ __forceinline__ void wg_fence(){ asm volatile("wgmma.fence.sync.aligned;":::"memory"); }
__device__ __forceinline__ void wg_commit(){ asm volatile("wgmma.commit_group.sync.aligned;":::"memory"); }
template<int N> __device__ __forceinline__ void wg_wait(){ asm volatile("wgmma.wait_group.sync.aligned %0;"::"n"(N):"memory"); }
template<int N> __device__ __forceinline__ void fence_regs(float (&d)[N]){
  #pragma unroll
  for(int i=0;i<N;i++) asm volatile("":"+f"(d[i])::"memory");
}
template<int N> __device__ __forceinline__ void def_regs(float (&d)[N]){
  #pragma unroll
  for(int i=0;i<N;i++) asm volatile("":"=f"(d[i]));
}
__device__ __forceinline__ uint64_t make_desc(uint32_t addr, uint32_t lbo, uint32_t sbo, uint32_t layout=1){
  uint64_t d = 0; d |= (uint64_t)((addr & 0x3FFFF)>>4); d |= (uint64_t)((lbo>>4)&0x3FFF)<<16; d |= (uint64_t)((sbo>>4)&0x3FFF)<<32; d |= (uint64_t)layout<<62; return d; }
__device__ __forceinline__ uint32_t pack_bf16(float lo, float hi){ uint32_t r; asm("cvt.rn.bf16x2.f32 %0, %1, %2;":"=r"(r):"f"(hi),"f"(lo)); return r; }
__device__ __forceinline__ float bf_lo(uint32_t v){ return __uint_as_float(v<<16); }
__device__ __forceinline__ float bf_hi(uint32_t v){ return __uint_as_float(v & 0xffff0000u); }
__device__ __forceinline__ void stmatrix_x4(uint32_t addr, uint32_t r0, uint32_t r1, uint32_t r2, uint32_t r3){
  asm volatile("stmatrix.sync.aligned.m8n8.x4.shared.b16 [%0], {%1,%2,%3,%4};"::"r"(addr),"r"(r0),"r"(r1),"r"(r2),"r"(r3):"memory");
}
__device__ __forceinline__ uint32_t lds_u16(uint32_t addr){ uint16_t v; asm volatile("ld.shared.u16 %0, [%1];":"=h"(v):"r"(addr)); return v; }
__device__ __forceinline__ float4 lds_f4(uint32_t addr){ float4 v; asm volatile("ld.shared.v4.f32 {%0,%1,%2,%3}, [%4];":"=f"(v.x),"=f"(v.y),"=f"(v.z),"=f"(v.w):"r"(addr)); return v; }

__device__ __forceinline__ uint32_t desc_lo(uint32_t addr, uint32_t lbo){ return ((addr & 0x3FFFF)>>4) | ((lbo>>4)<<16); }
template<uint32_t SBO, uint32_t LAYOUT=1> __device__ __forceinline__ uint64_t mk_desc(uint32_t lo){
  constexpr uint32_t hi = ((SBO>>4)&0x3FFF) | (LAYOUT<<30);
  uint64_t d; asm("mov.b64 %0, {%1, %2};":"=l"(d):"r"(lo),"n"(hi)); return d; }

__device__ __forceinline__ void stg128(void* p, uint4 v){ asm volatile("st.global.v4.b32 [%0], {%1,%2,%3,%4};"::"l"(p),"r"(v.x),"r"(v.y),"r"(v.z),"r"(v.w):"memory"); }
__device__ __forceinline__ uint4 quad_transpose(uint32_t a0, uint32_t a1, uint32_t a2, uint32_t a3, int t){
  const bool o = t&1, h = t&2;
  const uint32_t r0 = __shfl_xor_sync(0xffffffffu, o? a0 : a1, 1), r1 = __shfl_xor_sync(0xffffffffu, o? a2 : a3, 1);
  const uint32_t c0 = o? r0 : a0, c1 = o? a1 : r0, c2 = o? r1 : a2, c3 = o? a3 : r1;
  const uint32_t q0 = __shfl_xor_sync(0xffffffffu, h? c0 : c2, 2), q1 = __shfl_xor_sync(0xffffffffu, h? c1 : c3, 2);
  return h? make_uint4(q0,q1,c2,c3) : make_uint4(c0,c1,q0,q1);
}

alignas(128) __device__ const uint32_t T_F128[8192] = {
0x3f803f80,0x3f7b3f80,0x3f803f80,0xbe480000,0x3f803f80,0x3f553f6d,0x3f803f80,0xbf0ebec4,0x3f803f80,0x3f0e3f35,0x3f803f80,0xbf55bf35,
0x3f803f80,0x3e483ec4,0x3f803f80,0xbf7bbf6d,0xbf803f80,0xbe480000,0xbf803f80,0xbf7bbf80,0xbf803f80,0xbf0ebec4,0xbf803f80,0xbf55bf6d,
0xbf803f80,0xbf55bf35,0xbf803f80,0xbf0ebf35,0xbf803f80,0xbf7bbf6d,0xbf803f80,0xbe48bec4,0x3f803f80,0x3f783f80,0x3f673f6d,0xbf18bec4,
0x3f7d3f7f,0x3f3e3f62,0x3f5c3f62,0xbf67bf46,0x3f783f7b,0x3eac3f0e,0x3f4e3f55,0xbf80bf7b,0x3f713f75,0xbe163dc9,0x3f3e3f46,0xbf5cbf75,
0xbd490000,0xbe790000,0xbedbbec4,0xbf4ebf6d,0xbe16bdc9,0xbf2cbef1,0xbf04bef1,0xbedbbf22,0xbe79be48,0xbf71bf55,0xbf18bf0e,0x3d49be48,
0xbeacbe95,0xbf7dbf7f,0xbf2cbf22,0x3f043e95,0x3f7f3f80,0x3f753f80,0x3f223f35,0xbf62bf35,0x3f753f7b,0x3f223f55,0x3ef13f0e,0xbf7fbf7b,
0x3f623f6d,0x3dc93ec4,0x3e953ec4,0xbf46bf6d,0x3f463f55,0xbef1be48,0x3dc93e48,0xbe95bf0e,0xbdc90000,0xbe950000,0xbf46bf35,0xbef1bf35,
0xbe95be48,0xbf46bf0e,0xbf62bf55,0x3dc9be48,0xbef1bec4,0xbf7fbf6d,0xbf75bf6d,0x3f223ec4,0xbf22bf0e,0xbf62bf7b,0xbf7fbf7b,0x3f753f55,
0x3f7d3f80,0x3f713f80,0x3e793ec4,0xbf80bf6d,0x3f673f75,0x3f043f46,0xbd493dc9,0xbf4ebf75,0x3f3e3f55,0xbe163e48,0xbeacbe48,0xbe79bf0e,
0x3f043f22,0xbf3ebef1,0xbf18bef1,0x3edb3dc9,0xbe160000,0xbeac0000,0xbf78bf6d,0xbd49bec4,0xbedbbe95,0xbf5cbf22,0xbf80bf7f,0x3f183e95,
0xbf2cbf0e,0xbf7dbf7b,0xbf71bf7b,0x3f783f55,0xbf5cbf46,0xbf2cbf62,0xbf4ebf62,0x3f673f7f,0x3f803f80,0xbf7bbf80,0x3f803f80,0x3e480000,
0x3f803f80,0xbf55bf6d,0x3f803f80,0x3f0e3ec4,0x3f803f80,0xbf0ebf35,0x3f803f80,0x3f553f35,0x3f803f80,0xbe48bec4,0x3f803f80,0x3f7b3f6d,
0xbf803f80,0x3e480000,0xbf803f80,0x3f7b3f80,0xbf803f80,0x3f0e3ec4,0xbf803f80,0x3f553f6d,0xbf803f80,0x3f553f35,0xbf803f80,0x3f0e3f35,
0xbf803f80,0x3f7b3f6d,0xbf803f80,0x3e483ec4,0x3f2c3f35,0xbf04bf35,0x3eac3ec4,0x3f7d3f6d,0x3f183f22,0xbd49be95,0x3e793e95,0x3f713f7f,
0x3f043f0e,0x3edb3e48,0x3e163e48,0x3f2c3f55,0x3edb3ef1,0x3f4e3f22,0x3d493dc9,0x3e793ef1,0xbf3ebf35,0x3f5c3f35,0xbf71bf6d,0x3e163ec4,
0xbf4ebf46,0x3f803f75,0xbf78bf75,0xbeacbdc9,0xbf5cbf55,0x3f673f7b,0xbf7dbf7b,0xbf3ebf0e,0xbf67bf62,0x3f183f46,0xbf80bf7f,0xbf78bf62,
0xbdc90000,0x3e950000,0xbf46bf35,0x3ef13f35,0xbe95be48,0x3f463f0e,0xbf62bf55,0xbdc93e48,0xbef1bec4,0x3f7f3f6d,0xbf75bf6d,0xbf22bec4,
0xbf22bf0e,0x3f623f7b,0xbf7fbf7b,0xbf75bf55,0xbf7fbf80,0x3f753f80,0xbf22bf35,0xbf62bf35,0xbf75bf7b,0x3f223f55,0xbef1bf0e,0xbf7fbf7b,
0xbf62bf6d,0x3dc93ec4,0xbe95bec4,0xbf46bf6d,0xbf46bf55,0xbef1be48,0xbdc9be48,0xbe95bf0e,0xbf4ebf35,0x3f673f35,0xbf5cbf6d,0xbf2cbec4,
0xbf71bf62,0x3f783f7f,0xbf2cbf46,0xbf7dbf62,0xbf80bf7b,0x3f183f55,0xbedbbf0e,0xbf5cbf7b,0xbf78bf7f,0xbd493e95,0xbe16be95,0xbeacbf22,
0xbf18bf35,0x3edb3f35,0x3f043ec4,0xbf3ebf6d,0xbeacbef1,0xbe793dc9,0x3f3e3f22,0xbe16bef1,0xbd49be48,0xbf4ebf0e,0x3f673f55,0x3f043e48,
0x3e793dc9,0xbf80bf75,0x3f7d3f75,0x3f713f46,0x3f803f80,0x3f7b3f80,0x3f803f80,0xbe480000,0x3f803f80,0x3f553f6d,0x3f803f80,0xbf0ebec4,
0x3f803f80,0x3f0e3f35,0x3f803f80,0xbf55bf35,0x3f803f80,0x3e483ec4,0x3f803f80,0xbf7bbf6d,0xbf803f80,0xbe480000,0xbf803f80,0xbf7bbf80,
0xbf803f80,0xbf0ebec4,0xbf803f80,0xbf55bf6d,0xbf803f80,0xbf55bf35,0xbf803f80,0xbf0ebf35,0xbf803f80,0xbf7bbf6d,0xbf803f80,0xbe48bec4,
0xbd490000,0xbe790000,0xbedbbec4,0xbf4ebf6d,0xbe16bdc9,0xbf2cbef1,0xbf04bef1,0xbedbbf22,0xbe79be48,0xbf71bf55,0xbf18bf0e,0x3d49be48,
0xbeacbe95,0xbf7dbf7f,0xbf2cbf22,0x3f043e95,0xbf80bf80,0xbf78bf80,0xbf67bf6d,0x3f183ec4,0xbf7dbf7f,0xbf3ebf62,0xbf5cbf62,0x3f673f46,
0xbf78bf7b,0xbeacbf0e,0xbf4ebf55,0x3f803f7b,0xbf71bf75,0x3e16bdc9,0xbf3ebf46,0x3f5c3f75,0xbf7fbf80,0xbf75bf80,0xbf22bf35,0x3f623f35,
0xbf75bf7b,0xbf22bf55,0xbef1bf0e,0x3f7f3f7b,0xbf62bf6d,0xbdc9bec4,0xbe95bec4,0x3f463f6d,0xbf46bf55,0x3ef13e48,0xbdc9be48,0x3e953f0e,
0x3dc90000,0x3e950000,0x3f463f35,0x3ef13f35,0x3e953e48,0x3f463f0e,0x3f623f55,0xbdc93e48,0x3ef13ec4,0x3f7f3f6d,0x3f753f6d,0xbf22bec4,
0x3f223f0e,0x3f623f7b,0x3f7f3f7b,0xbf75bf55,0x3e160000,0x3eac0000,0x3f783f6d,0x3d493ec4,0x3edb3e95,0x3f5c3f22,0x3f803f7f,0xbf18be95,
0x3f2c3f0e,0x3f7d3f7b,0x3f713f7b,0xbf78bf55,0x3f5c3f46,0x3f2c3f62,0x3f4e3f62,0xbf67bf7f,0x3f7d3f80,0x3f713f80,0x3e793ec4,0xbf80bf6d,
0x3f673f75,0x3f043f46,0xbd493dc9,0xbf4ebf75,0x3f3e3f55,0xbe163e48,0xbeacbe48,0xbe79bf0e,0x3f043f22,0xbf3ebef1,0xbf18bef1,0x3edb3dc9,
0x3f803f80,0xbf7bbf80,0x3f803f80,0x3e480000,0x3f803f80,0xbf55bf6d,0x3f803f80,0x3f0e3ec4,0x3f803f80,0xbf0ebf35,0x3f803f80,0x3f553f35,
0x3f803f80,0xbe48bec4,0x3f803f80,0x3f7b3f6d,0xbf803f80,0x3e480000,0xbf803f80,0x3f7b3f80,0xbf803f80,0x3f0e3ec4,0xbf803f80,0x3f553f6d,
0xbf803f80,0x3f553f35,0xbf803f80,0x3f0e3f35,0xbf803f80,0x3f7b3f6d,0xbf803f80,0x3e483ec4,0xbf3ebf35,0x3f5c3f35,0xbf71bf6d,0x3e163ec4,
0xbf4ebf46,0x3f803f75,0xbf78bf75,0xbeacbdc9,0xbf5cbf55,0x3f673f7b,0xbf7dbf7b,0xbf3ebf0e,0xbf67bf62,0x3f183f46,0xbf80bf7f,0xbf78bf62,
0xbf2cbf35,0x3f043f35,0xbeacbec4,0xbf7dbf6d,0xbf18bf22,0x3d493e95,0xbe79be95,0xbf71bf7f,0xbf04bf0e,0xbedbbe48,0xbe16be48,0xbf2cbf55,
0xbedbbef1,0xbf4ebf22,0xbd49bdc9,0xbe79bef1,0x3dc90000,0xbe950000,0x3f463f35,0xbef1bf35,0x3e953e48,0xbf46bf0e,0x3f623f55,0x3dc9be48,
0x3ef13ec4,0xbf7fbf6d,0x3f753f6d,0x3f223ec4,0x3f223f0e,0xbf62bf7b,0x3f7f3f7b,0x3f753f55,0x3f7f3f80,0xbf75bf80,0x3f223f35,0x3f623f35,
0x3f753f7b,0xbf22bf55,0x3ef13f0e,0x3f7f3f7b,0x3f623f6d,0xbdc9bec4,0x3e953ec4,0x3f463f6d,0x3f463f55,0x3ef13e48,0x3dc93e48,0x3e953f0e,
0x3f183f35,0xbedbbf35,0xbf04bec4,0x3f3e3f6d,0x3eac3ef1,0x3e79bdc9,0xbf3ebf22,0x3e163ef1,0x3d493e48,0x3f4e3f0e,0xbf67bf55,0xbf04be48,
0xbe79bdc9,0x3f803f75,0xbf7dbf75,0xbf71bf46,0xbf4ebf35,0x3f673f35,0xbf5cbf6d,0xbf2cbec4,0xbf71bf62,0x3f783f7f,0xbf2cbf46,0xbf7dbf62,
0xbf80bf7b,0x3f183f55,0xbedbbf0e,0xbf5cbf7b,0xbf78bf7f,0xbd493e95,0xbe16be95,0xbeacbf22,0x3f803f80,0x3f7b3f80,0x3f803f80,0xbe480000,
0x3f803f80,0x3f553f6d,0x3f803f80,0xbf0ebec4,0x3f803f80,0x3f0e3f35,0x3f803f80,0xbf55bf35,0x3f803f80,0x3e483ec4,0x3f803f80,0xbf7bbf6d,
0xbf803f80,0xbe480000,0xbf803f80,0xbf7bbf80,0xbf803f80,0xbf0ebec4,0xbf803f80,0xbf55bf6d,0xbf803f80,0xbf55bf35,0xbf803f80,0xbf0ebf35,
0xbf803f80,0xbf7bbf6d,0xbf803f80,0xbe48bec4,0xbf80bf80,0xbf78bf80,0xbf67bf6d,0x3f183ec4,0xbf7dbf7f,0xbf3ebf62,0xbf5cbf62,0x3f673f46,
0xbf78bf7b,0xbeacbf0e,0xbf4ebf55,0x3f803f7b,0xbf71bf75,0x3e16bdc9,0xbf3ebf46,0x3f5c3f75,0x3d490000,0x3e790000,0x3edb3ec4,0x3f4e3f6d,
0x3e163dc9,0x3f2c3ef1,0x3f043ef1,0x3edb3f22,0x3e793e48,0x3f713f55,0x3f183f0e,0xbd493e48,0x3eac3e95,0x3f7d3f7f,0x3f2c3f22,0xbf04be95,
0x3f7f3f80,0x3f753f80,0x3f223f35,0xbf62bf35,0x3f753f7b,0x3f223f55,0x3ef13f0e,0xbf7fbf7b,0x3f623f6d,0x3dc93ec4,0x3e953ec4,0xbf46bf6d,
0x3f463f55,0xbef1be48,0x3dc93e48,0xbe95bf0e,0xbdc90000,0xbe950000,0xbf46bf35,0xbef1bf35,0xbe95be48,0xbf46bf0e,0xbf62bf55,0x3dc9be48,
0xbef1bec4,0xbf7fbf6d,0xbf75bf6d,0x3f223ec4,0xbf22bf0e,0xbf62bf7b,0xbf7fbf7b,0x3f753f55,0xbf7dbf80,0xbf71bf80,0xbe79bec4,0x3f803f6d,
0xbf67bf75,0xbf04bf46,0x3d49bdc9,0x3f4e3f75,0xbf3ebf55,0x3e16be48,0x3eac3e48,0x3e793f0e,0xbf04bf22,0x3f3e3ef1,0x3f183ef1,0xbedbbdc9,
0x3e160000,0x3eac0000,0x3f783f6d,0x3d493ec4,0x3edb3e95,0x3f5c3f22,0x3f803f7f,0xbf18be95,0x3f2c3f0e,0x3f7d3f7b,0x3f713f7b,0xbf78bf55,
0x3f5c3f46,0x3f2c3f62,0x3f4e3f62,0xbf67bf7f,0x3f803f80,0xbf7bbf80,0x3f803f80,0x3e480000,0x3f803f80,0xbf55bf6d,0x3f803f80,0x3f0e3ec4,
0x3f803f80,0xbf0ebf35,0x3f803f80,0x3f553f35,0x3f803f80,0xbe48bec4,0x3f803f80,0x3f7b3f6d,0xbf803f80,0x3e480000,0xbf803f80,0x3f7b3f80,
0xbf803f80,0x3f0e3ec4,0xbf803f80,0x3f553f6d,0xbf803f80,0x3f553f35,0xbf803f80,0x3f0e3f35,0xbf803f80,0x3f7b3f6d,0xbf803f80,0x3e483ec4,
0xbf2cbf35,0x3f043f35,0xbeacbec4,0xbf7dbf6d,0xbf18bf22,0x3d493e95,0xbe79be95,0xbf71bf7f,0xbf04bf0e,0xbedbbe48,0xbe16be48,0xbf2cbf55,
0xbedbbef1,0xbf4ebf22,0xbd49bdc9,0xbe79bef1,0x3f3e3f35,0xbf5cbf35,0x3f713f6d,0xbe16bec4,0x3f4e3f46,0xbf80bf75,0x3f783f75,0x3eac3dc9,
0x3f5c3f55,0xbf67bf7b,0x3f7d3f7b,0x3f3e3f0e,0x3f673f62,0xbf18bf46,0x3f803f7f,0x3f783f62,0xbdc90000,0x3e950000,0xbf46bf35,0x3ef13f35,
0xbe95be48,0x3f463f0e,0xbf62bf55,0xbdc93e48,0xbef1bec4,0x3f7f3f6d,0xbf75bf6d,0xbf22bec4,0xbf22bf0e,0x3f623f7b,0xbf7fbf7b,0xbf75bf55,
0xbf7fbf80,0x3f753f80,0xbf22bf35,0xbf62bf35,0xbf75bf7b,0x3f223f55,0xbef1bf0e,0xbf7fbf7b,0xbf62bf6d,0x3dc93ec4,0xbe95bec4,0xbf46bf6d,
0xbf46bf55,0xbef1be48,0xbdc9be48,0xbe95bf0e,0x3f4e3f35,0xbf67bf35,0x3f5c3f6d,0x3f2c3ec4,0x3f713f62,0xbf78bf7f,0x3f2c3f46,0x3f7d3f62,
0x3f803f7b,0xbf18bf55,0x3edb3f0e,0x3f5c3f7b,0x3f783f7f,0x3d49be95,0x3e163e95,0x3eac3f22,0x3f183f35,0xbedbbf35,0xbf04bec4,0x3f3e3f6d,
0x3eac3ef1,0x3e79bdc9,0xbf3ebf22,0x3e163ef1,0x3d493e48,0x3f4e3f0e,0xbf67bf55,0xbf04be48,0xbe79bdc9,0x3f803f75,0xbf7dbf75,0xbf71bf46,
0x3f803f80,0x3f7b3f80,0x3f803f80,0xbe480000,0x3f803f80,0x3f553f6d,0x3f803f80,0xbf0ebec4,0x3f803f80,0x3f0e3f35,0x3f803f80,0xbf55bf35,
0x3f803f80,0x3e483ec4,0x3f803f80,0xbf7bbf6d,0xbf803f80,0xbe480000,0xbf803f80,0xbf7bbf80,0xbf803f80,0xbf0ebec4,0xbf803f80,0xbf55bf6d,
0xbf803f80,0xbf55bf35,0xbf803f80,0xbf0ebf35,0xbf803f80,0xbf7bbf6d,0xbf803f80,0xbe48bec4,0x3d490000,0x3e790000,0x3edb3ec4,0x3f4e3f6d,
0x3e163dc9,0x3f2c3ef1,0x3f043ef1,0x3edb3f22,0x3e793e48,0x3f713f55,0x3f183f0e,0xbd493e48,0x3eac3e95,0x3f7d3f7f,0x3f2c3f22,0xbf04be95,
0x3f803f80,0x3f783f80,0x3f673f6d,0xbf18bec4,0x3f7d3f7f,0x3f3e3f62,0x3f5c3f62,0xbf67bf46,0x3f783f7b,0x3eac3f0e,0x3f4e3f55,0xbf80bf7b,
0x3f713f75,0xbe163dc9,0x3f3e3f46,0xbf5cbf75,0xbf7fbf80,0xbf75bf80,0xbf22bf35,0x3f623f35,0xbf75bf7b,0xbf22bf55,0xbef1bf0e,0x3f7f3f7b,
0xbf62bf6d,0xbdc9bec4,0xbe95bec4,0x3f463f6d,0xbf46bf55,0x3ef13e48,0xbdc9be48,0x3e953f0e,0x3dc90000,0x3e950000,0x3f463f35,0x3ef13f35,
0x3e953e48,0x3f463f0e,0x3f623f55,0xbdc93e48,0x3ef13ec4,0x3f7f3f6d,0x3f753f6d,0xbf22bec4,0x3f223f0e,0x3f623f7b,0x3f7f3f7b,0xbf75bf55,
0xbe160000,0xbeac0000,0xbf78bf6d,0xbd49bec4,0xbedbbe95,0xbf5cbf22,0xbf80bf7f,0x3f183e95,0xbf2cbf0e,0xbf7dbf7b,0xbf71bf7b,0x3f783f55,
0xbf5cbf46,0xbf2cbf62,0xbf4ebf62,0x3f673f7f,0xbf7dbf80,0xbf71bf80,0xbe79bec4,0x3f803f6d,0xbf67bf75,0xbf04bf46,0x3d49bdc9,0x3f4e3f75,
0xbf3ebf55,0x3e16be48,0x3eac3e48,0x3e793f0e,0xbf04bf22,0x3f3e3ef1,0x3f183ef1,0xbedbbdc9,0x3f803f80,0xbf7bbf80,0x3f803f80,0x3e480000,
0x3f803f80,0xbf55bf6d,0x3f803f80,0x3f0e3ec4,0x3f803f80,0xbf0ebf35,0x3f803f80,0x3f553f35,0x3f803f80,0xbe48bec4,0x3f803f80,0x3f7b3f6d,
0xbf803f80,0x3e480000,0xbf803f80,0x3f7b3f80,0xbf803f80,0x3f0e3ec4,0xbf803f80,0x3f553f6d,0xbf803f80,0x3f553f35,0xbf803f80,0x3f0e3f35,
0xbf803f80,0x3f7b3f6d,0xbf803f80,0x3e483ec4,0x3f3e3f35,0xbf5cbf35,0x3f713f6d,0xbe16bec4,0x3f4e3f46,0xbf80bf75,0x3f783f75,0x3eac3dc9,
0x3f5c3f55,0xbf67bf7b,0x3f7d3f7b,0x3f3e3f0e,0x3f673f62,0xbf18bf46,0x3f803f7f,0x3f783f62,0x3f2c3f35,0xbf04bf35,0x3eac3ec4,0x3f7d3f6d,
0x3f183f22,0xbd49be95,0x3e793e95,0x3f713f7f,0x3f043f0e,0x3edb3e48,0x3e163e48,0x3f2c3f55,0x3edb3ef1,0x3f4e3f22,0x3d493dc9,0x3e793ef1,
0x3dc90000,0xbe950000,0x3f463f35,0xbef1bf35,0x3e953e48,0xbf46bf0e,0x3f623f55,0x3dc9be48,0x3ef13ec4,0xbf7fbf6d,0x3f753f6d,0x3f223ec4,
0x3f223f0e,0xbf62bf7b,0x3f7f3f7b,0x3f753f55,0x3f7f3f80,0xbf75bf80,0x3f223f35,0x3f623f35,0x3f753f7b,0xbf22bf55,0x3ef13f0e,0x3f7f3f7b,
0x3f623f6d,0xbdc9bec4,0x3e953ec4,0x3f463f6d,0x3f463f55,0x3ef13e48,0x3dc93e48,0x3e953f0e,0xbf18bf35,0x3edb3f35,0x3f043ec4,0xbf3ebf6d,
0xbeacbef1,0xbe793dc9,0x3f3e3f22,0xbe16bef1,0xbd49be48,0xbf4ebf0e,0x3f673f55,0x3f043e48,0x3e793dc9,0xbf80bf75,0x3f7d3f75,0x3f713f46,
0x3f4e3f35,0xbf67bf35,0x3f5c3f6d,0x3f2c3ec4,0x3f713f62,0xbf78bf7f,0x3f2c3f46,0x3f7d3f62,0x3f803f7b,0xbf18bf55,0x3edb3f0e,0x3f5c3f7b,
0x3f783f7f,0x3d49be95,0x3e163e95,0x3eac3f22,0x3f6d3f80,0x3f553f80,0xbf6dbf80,0x3f0e0000,0x3ec43f35,0xbe483ec4,0xbec4bf35,0x3f7b3f6d,
0xbec40000,0xbf7bbf35,0x3ec40000,0x3e483f35,0xbf6dbf35,0xbf0ebf6d,0x3f6d3f35,0xbf55bec4,0xbec40000,0xbf0e0000,0x3ec40000,0x3f553f80,
0xbf6dbf35,0xbf7bbf6d,0x3f6d3f35,0xbe483ec4,0xbf6dbf80,0xbe48bf35,0x3f6d3f80,0xbf7bbf35,0xbec4bf35,0x3f553ec4,0x3ec43f35,0xbf0ebf6d,
0x3f673f80,0x3f4e3f80,0xbf2cbf6d,0x3f5c3ec4,0x3e793f22,0xbeac3e95,0x3e16be95,0x3f3e3f7f,0xbf18be48,0xbf80bf55,0x3f5c3f0e,0xbedb3e48,
0xbf80bf62,0xbe79bf46,0x3f713f7f,0xbf7dbf62,0xbedb0000,0xbf180000,0x3f3e3ec4,0x3f043f6d,0xbf78bf46,0xbf71bf75,0x3f7d3f75,0xbf2cbdc9,
0xbf4ebf7b,0x3d49bf0e,0x3f043f55,0xbf67bf7b,0xbd49bef1,0x3f783f22,0xbeac3dc9,0x3e16bef1,0x3f623f80,0x3f463f80,0xbe95bf35,0x3f7f3f35,
0x3dc93f0e,0xbef13e48,0x3f223e48,0x3e953f55,0xbf46bec4,0xbf75bf6d,0x3f7f3f6d,0xbf62bec4,0xbf75bf7b,0x3dc9bf0e,0x3ef13f55,0xbf22bf7b,
0xbef10000,0xbf220000,0x3f753f35,0x3dc93f35,0xbf7fbf55,0xbf62bf7b,0x3f463f7b,0xbf75bf0e,0xbf22bf6d,0x3e95bec4,0xbdc93ec4,0xbef1bf6d,
0x3e95be48,0x3f7f3f55,0xbf62bf0e,0x3f463e48,0x3f5c3f80,0x3f3e3f80,0x3e16bec4,0x3f713f6d,0xbd493ef1,0xbf183dc9,0x3f713f22,0xbe793ef1,
0xbf67bf0e,0xbf5cbf7b,0x3f3e3f7b,0xbf7dbf55,0xbf4ebf7f,0x3edbbe95,0xbe793e95,0x3d49bf22,0xbf040000,0xbf2c0000,0x3f7d3f6d,0xbeac3ec4,
0xbf80bf62,0xbf4ebf7f,0x3eac3f46,0xbf78bf62,0xbedbbf55,0x3f04be48,0xbf2cbe48,0x3e16bf0e,0x3f183dc9,0x3f673f75,0xbf78bf75,0x3f803f46,
0x3f6d3f80,0xbf55bf80,0xbf6dbf80,0xbf0e0000,0x3ec43f35,0x3e48bec4,0xbec4bf35,0xbf7bbf6d,0xbec40000,0x3f7b3f35,0x3ec40000,0xbe48bf35,
0xbf6dbf35,0x3f0e3f6d,0x3f6d3f35,0x3f553ec4,0xbec40000,0x3f0e0000,0x3ec40000,0xbf55bf80,0xbf6dbf35,0x3f7b3f6d,0x3f6d3f35,0x3e48bec4,
0xbf6dbf80,0x3e483f35,0x3f6d3f80,0x3f7b3f35,0xbec4bf35,0xbf55bec4,0x3ec43f35,0x3f0e3f6d,0x3eac3f35,0xbe16bf35,0x3d49bec4,0xbf78bf6d,
0xbf04bdc9,0x3f673ef1,0x3f4e3ef1,0xbd49bf22,0xbf7dbf55,0x3f2c3f7b,0x3f783f7b,0x3f713f0e,0xbf3ebf75,0xbf043dc9,0x3edb3f46,0x3f183f75,
0xbf71bf35,0x3f7d3f35,0x3f803f6d,0x3e79bec4,0xbf5cbf7f,0x3edb3f62,0x3f183f62,0x3f803f46,0xbe16bf0e,0xbf3ebe48,0xbe793e48,0x3eac3f55,
0x3f2c3e95,0xbf5cbf7f,0xbf67bf22,0xbf4ebe95,0xbef10000,0x3f220000,0x3f753f35,0xbdc9bf35,0xbf7fbf55,0x3f623f7b,0x3f463f7b,0x3f753f0e,
0xbf22bf6d,0xbe953ec4,0xbdc93ec4,0x3ef13f6d,0x3e95be48,0xbf7fbf55,0xbf62bf0e,0xbf46be48,0xbf62bf80,0x3f463f80,0x3e953f35,0x3f7f3f35,
0xbdc9bf0e,0xbef13e48,0xbf22be48,0x3e953f55,0x3f463ec4,0xbf75bf6d,0xbf7fbf6d,0xbf62bec4,0x3f753f7b,0x3dc9bf0e,0xbef1bf55,0xbf22bf7b,
0xbf78bf35,0x3f803f35,0x3f183f6d,0x3f673ec4,0xbf2cbf75,0x3e163f46,0xbedb3dc9,0x3f043f75,0x3eacbe48,0xbf78bf0e,0xbf80bf55,0xbf4ebe48,
0x3f7d3f46,0xbeacbf62,0xbf04bf62,0xbf2cbf7f,0xbe79bf35,0x3d493f35,0xbf4ebec4,0x3edb3f6d,0x3f3e3e95,0xbf7dbf22,0xbf67bf7f,0xbf5cbe95,
0x3f713f7b,0xbe79bf55,0xbd49bf0e,0xbf18bf7b,0x3e163f22,0x3f713ef1,0x3f5c3ef1,0x3f3e3dc9,0x3f6d3f80,0x3f553f80,0xbf6dbf80,0x3f0e0000,
0x3ec43f35,0xbe483ec4,0xbec4bf35,0x3f7b3f6d,0xbec40000,0xbf7bbf35,0x3ec40000,0x3e483f35,0xbf6dbf35,0xbf0ebf6d,0x3f6d3f35,0xbf55bec4,
0xbec40000,0xbf0e0000,0x3ec40000,0x3f553f80,0xbf6dbf35,0xbf7bbf6d,0x3f6d3f35,0xbe483ec4,0xbf6dbf80,0xbe48bf35,0x3f6d3f80,0xbf7bbf35,
0xbec4bf35,0x3f553ec4,0x3ec43f35,0xbf0ebf6d,0xbedb0000,0xbf180000,0x3f3e3ec4,0x3f043f6d,0xbf78bf46,0xbf71bf75,0x3f7d3f75,0xbf2cbdc9,
0xbf4ebf7b,0x3d49bf0e,0x3f043f55,0xbf67bf7b,0xbd49bef1,0x3f783f22,0xbeac3dc9,0x3e16bef1,0xbf67bf80,0xbf4ebf80,0x3f2c3f6d,0xbf5cbec4,
0xbe79bf22,0x3eacbe95,0xbe163e95,0xbf3ebf7f,0x3f183e48,0x3f803f55,0xbf5cbf0e,0x3edbbe48,0x3f803f62,0x3e793f46,0xbf71bf7f,0x3f7d3f62,
0xbf62bf80,0xbf46bf80,0x3e953f35,0xbf7fbf35,0xbdc9bf0e,0x3ef1be48,0xbf22be48,0xbe95bf55,0x3f463ec4,0x3f753f6d,0xbf7fbf6d,0x3f623ec4,
0x3f753f7b,0xbdc93f0e,0xbef1bf55,0x3f223f7b,0x3ef10000,0x3f220000,0xbf75bf35,0xbdc9bf35,0x3f7f3f55,0x3f623f7b,0xbf46bf7b,0x3f753f0e,
0x3f223f6d,0xbe953ec4,0x3dc9bec4,0x3ef13f6d,0xbe953e48,0xbf7fbf55,0x3f623f0e,0xbf46be48,0x3f040000,0x3f2c0000,0xbf7dbf6d,0x3eacbec4,
0x3f803f62,0x3f4e3f7f,0xbeacbf46,0x3f783f62,0x3edb3f55,0xbf043e48,0x3f2c3e48,0xbe163f0e,0xbf18bdc9,0xbf67bf75,0x3f783f75,0xbf80bf46,
0x3f5c3f80,0x3f3e3f80,0x3e16bec4,0x3f713f6d,0xbd493ef1,0xbf183dc9,0x3f713f22,0xbe793ef1,0xbf67bf0e,0xbf5cbf7b,0x3f3e3f7b,0xbf7dbf55,
0xbf4ebf7f,0x3edbbe95,0xbe793e95,0x3d49bf22,0x3f6d3f80,0xbf55bf80,0xbf6dbf80,0xbf0e0000,0x3ec43f35,0x3e48bec4,0xbec4bf35,0xbf7bbf6d,
0xbec40000,0x3f7b3f35,0x3ec40000,0xbe48bf35,0xbf6dbf35,0x3f0e3f6d,0x3f6d3f35,0x3f553ec4,0xbec40000,0x3f0e0000,0x3ec40000,0xbf55bf80,
0xbf6dbf35,0x3f7b3f6d,0x3f6d3f35,0x3e48bec4,0xbf6dbf80,0x3e483f35,0x3f6d3f80,0x3f7b3f35,0xbec4bf35,0xbf55bec4,0x3ec43f35,0x3f0e3f6d,
0xbf71bf35,0x3f7d3f35,0x3f803f6d,0x3e79bec4,0xbf5cbf7f,0x3edb3f62,0x3f183f62,0x3f803f46,0xbe16bf0e,0xbf3ebe48,0xbe793e48,0x3eac3f55,
0x3f2c3e95,0xbf5cbf7f,0xbf67bf22,0xbf4ebe95,0xbeacbf35,0x3e163f35,0xbd493ec4,0x3f783f6d,0x3f043dc9,0xbf67bef1,0xbf4ebef1,0x3d493f22,
0x3f7d3f55,0xbf2cbf7b,0xbf78bf7b,0xbf71bf0e,0x3f3e3f75,0x3f04bdc9,0xbedbbf46,0xbf18bf75,0x3ef10000,0xbf220000,0xbf75bf35,0x3dc93f35,
0x3f7f3f55,0xbf62bf7b,0xbf46bf7b,0xbf75bf0e,0x3f223f6d,0x3e95bec4,0x3dc9bec4,0xbef1bf6d,0xbe953e48,0x3f7f3f55,0x3f623f0e,0x3f463e48,
0x3f623f80,0xbf46bf80,0xbe95bf35,0xbf7fbf35,0x3dc93f0e,0x3ef1be48,0x3f223e48,0xbe95bf55,0xbf46bec4,0x3f753f6d,0x3f7f3f6d,0x3f623ec4,
0xbf75bf7b,0xbdc93f0e,0x3ef13f55,0x3f223f7b,0x3e793f35,0xbd49bf35,0x3f4e3ec4,0xbedbbf6d,0xbf3ebe95,0x3f7d3f22,0x3f673f7f,0x3f5c3e95,
0xbf71bf7b,0x3e793f55,0x3d493f0e,0x3f183f7b,0xbe16bf22,0xbf71bef1,0xbf5cbef1,0xbf3ebdc9,0xbf78bf35,0x3f803f35,0x3f183f6d,0x3f673ec4,
0xbf2cbf75,0x3e163f46,0xbedb3dc9,0x3f043f75,0x3eacbe48,0xbf78bf0e,0xbf80bf55,0xbf4ebe48,0x3f7d3f46,0xbeacbf62,0xbf04bf62,0xbf2cbf7f,
0x3f6d3f80,0x3f553f80,0xbf6dbf80,0x3f0e0000,0x3ec43f35,0xbe483ec4,0xbec4bf35,0x3f7b3f6d,0xbec40000,0xbf7bbf35,0x3ec40000,0x3e483f35,
0xbf6dbf35,0xbf0ebf6d,0x3f6d3f35,0xbf55bec4,0xbec40000,0xbf0e0000,0x3ec40000,0x3f553f80,0xbf6dbf35,0xbf7bbf6d,0x3f6d3f35,0xbe483ec4,
0xbf6dbf80,0xbe48bf35,0x3f6d3f80,0xbf7bbf35,0xbec4bf35,0x3f553ec4,0x3ec43f35,0xbf0ebf6d,0xbf67bf80,0xbf4ebf80,0x3f2c3f6d,0xbf5cbec4,
0xbe79bf22,0x3eacbe95,0xbe163e95,0xbf3ebf7f,0x3f183e48,0x3f803f55,0xbf5cbf0e,0x3edbbe48,0x3f803f62,0x3e793f46,0xbf71bf7f,0x3f7d3f62,
0x3edb0000,0x3f180000,0xbf3ebec4,0xbf04bf6d,0x3f783f46,0x3f713f75,0xbf7dbf75,0x3f2c3dc9,0x3f4e3f7b,0xbd493f0e,0xbf04bf55,0x3f673f7b,
0x3d493ef1,0xbf78bf22,0x3eacbdc9,0xbe163ef1,0x3f623f80,0x3f463f80,0xbe95bf35,0x3f7f3f35,0x3dc93f0e,0xbef13e48,0x3f223e48,0x3e953f55,
0xbf46bec4,0xbf75bf6d,0x3f7f3f6d,0xbf62bec4,0xbf75bf7b,0x3dc9bf0e,0x3ef13f55,0xbf22bf7b,0xbef10000,0xbf220000,0x3f753f35,0x3dc93f35,
0xbf7fbf55,0xbf62bf7b,0x3f463f7b,0xbf75bf0e,0xbf22bf6d,0x3e95bec4,0xbdc93ec4,0xbef1bf6d,0x3e95be48,0x3f7f3f55,0xbf62bf0e,0x3f463e48,
0xbf5cbf80,0xbf3ebf80,0xbe163ec4,0xbf71bf6d,0x3d49bef1,0x3f18bdc9,0xbf71bf22,0x3e79bef1,0x3f673f0e,0x3f5c3f7b,0xbf3ebf7b,0x3f7d3f55,
0x3f4e3f7f,0xbedb3e95,0x3e79be95,0xbd493f22,0x3f040000,0x3f2c0000,0xbf7dbf6d,0x3eacbec4,0x3f803f62,0x3f4e3f7f,0xbeacbf46,0x3f783f62,
0x3edb3f55,0xbf043e48,0x3f2c3e48,0xbe163f0e,0xbf18bdc9,0xbf67bf75,0x3f783f75,0xbf80bf46,0x3f6d3f80,0xbf55bf80,0xbf6dbf80,0xbf0e0000,
0x3ec43f35,0x3e48bec4,0xbec4bf35,0xbf7bbf6d,0xbec40000,0x3f7b3f35,0x3ec40000,0xbe48bf35,0xbf6dbf35,0x3f0e3f6d,0x3f6d3f35,0x3f553ec4,
0xbec40000,0x3f0e0000,0x3ec40000,0xbf55bf80,0xbf6dbf35,0x3f7b3f6d,0x3f6d3f35,0x3e48bec4,0xbf6dbf80,0x3e483f35,0x3f6d3f80,0x3f7b3f35,
0xbec4bf35,0xbf55bec4,0x3ec43f35,0x3f0e3f6d,0xbeacbf35,0x3e163f35,0xbd493ec4,0x3f783f6d,0x3f043dc9,0xbf67bef1,0xbf4ebef1,0x3d493f22,
0x3f7d3f55,0xbf2cbf7b,0xbf78bf7b,0xbf71bf0e,0x3f3e3f75,0x3f04bdc9,0xbedbbf46,0xbf18bf75,0x3f713f35,0xbf7dbf35,0xbf80bf6d,0xbe793ec4,
0x3f5c3f7f,0xbedbbf62,0xbf18bf62,0xbf80bf46,0x3e163f0e,0x3f3e3e48,0x3e79be48,0xbeacbf55,0xbf2cbe95,0x3f5c3f7f,0x3f673f22,0x3f4e3e95,
0xbef10000,0x3f220000,0x3f753f35,0xbdc9bf35,0xbf7fbf55,0x3f623f7b,0x3f463f7b,0x3f753f0e,0xbf22bf6d,0xbe953ec4,0xbdc93ec4,0x3ef13f6d,
0x3e95be48,0xbf7fbf55,0xbf62bf0e,0xbf46be48,0xbf62bf80,0x3f463f80,0x3e953f35,0x3f7f3f35,0xbdc9bf0e,0xbef13e48,0xbf22be48,0x3e953f55,
0x3f463ec4,0xbf75bf6d,0xbf7fbf6d,0xbf62bec4,0x3f753f7b,0x3dc9bf0e,0xbef1bf55,0xbf22bf7b,0x3f783f35,0xbf80bf35,0xbf18bf6d,0xbf67bec4,
0x3f2c3f75,0xbe16bf46,0x3edbbdc9,0xbf04bf75,0xbeac3e48,0x3f783f0e,0x3f803f55,0x3f4e3e48,0xbf7dbf46,0x3eac3f62,0x3f043f62,0x3f2c3f7f,
0x3e793f35,0xbd49bf35,0x3f4e3ec4,0xbedbbf6d,0xbf3ebe95,0x3f7d3f22,0x3f673f7f,0x3f5c3e95,0xbf71bf7b,0x3e793f55,0x3d493f0e,0x3f183f7b,
0xbe16bf22,0xbf71bef1,0xbf5cbef1,0xbf3ebdc9,0x3f6d3f80,0x3f553f80,0xbf6dbf80,0x3f0e0000,0x3ec43f35,0xbe483ec4,0xbec4bf35,0x3f7b3f6d,
0xbec40000,0xbf7bbf35,0x3ec40000,0x3e483f35,0xbf6dbf35,0xbf0ebf6d,0x3f6d3f35,0xbf55bec4,0xbec40000,0xbf0e0000,0x3ec40000,0x3f553f80,
0xbf6dbf35,0xbf7bbf6d,0x3f6d3f35,0xbe483ec4,0xbf6dbf80,0xbe48bf35,0x3f6d3f80,0xbf7bbf35,0xbec4bf35,0x3f553ec4,0x3ec43f35,0xbf0ebf6d,
0x3edb0000,0x3f180000,0xbf3ebec4,0xbf04bf6d,0x3f783f46,0x3f713f75,0xbf7dbf75,0x3f2c3dc9,0x3f4e3f7b,0xbd493f0e,0xbf04bf55,0x3f673f7b,
0x3d493ef1,0xbf78bf22,0x3eacbdc9,0xbe163ef1,0x3f673f80,0x3f4e3f80,0xbf2cbf6d,0x3f5c3ec4,0x3e793f22,0xbeac3e95,0x3e16be95,0x3f3e3f7f,
0xbf18be48,0xbf80bf55,0x3f5c3f0e,0xbedb3e48,0xbf80bf62,0xbe79bf46,0x3f713f7f,0xbf7dbf62,0xbf62bf80,0xbf46bf80,0x3e953f35,0xbf7fbf35,
0xbdc9bf0e,0x3ef1be48,0xbf22be48,0xbe95bf55,0x3f463ec4,0x3f753f6d,0xbf7fbf6d,0x3f623ec4,0x3f753f7b,0xbdc93f0e,0xbef1bf55,0x3f223f7b,
0x3ef10000,0x3f220000,0xbf75bf35,0xbdc9bf35,0x3f7f3f55,0x3f623f7b,0xbf46bf7b,0x3f753f0e,0x3f223f6d,0xbe953ec4,0x3dc9bec4,0x3ef13f6d,
0xbe953e48,0xbf7fbf55,0x3f623f0e,0xbf46be48,0xbf040000,0xbf2c0000,0x3f7d3f6d,0xbeac3ec4,0xbf80bf62,0xbf4ebf7f,0x3eac3f46,0xbf78bf62,
0xbedbbf55,0x3f04be48,0xbf2cbe48,0x3e16bf0e,0x3f183dc9,0x3f673f75,0xbf78bf75,0x3f803f46,0xbf5cbf80,0xbf3ebf80,0xbe163ec4,0xbf71bf6d,
0x3d49bef1,0x3f18bdc9,0xbf71bf22,0x3e79bef1,0x3f673f0e,0x3f5c3f7b,0xbf3ebf7b,0x3f7d3f55,0x3f4e3f7f,0xbedb3e95,0x3e79be95,0xbd493f22,
0x3f6d3f80,0xbf55bf80,0xbf6dbf80,0xbf0e0000,0x3ec43f35,0x3e48bec4,0xbec4bf35,0xbf7bbf6d,0xbec40000,0x3f7b3f35,0x3ec40000,0xbe48bf35,
0xbf6dbf35,0x3f0e3f6d,0x3f6d3f35,0x3f553ec4,0xbec40000,0x3f0e0000,0x3ec40000,0xbf55bf80,0xbf6dbf35,0x3f7b3f6d,0x3f6d3f35,0x3e48bec4,
0xbf6dbf80,0x3e483f35,0x3f6d3f80,0x3f7b3f35,0xbec4bf35,0xbf55bec4,0x3ec43f35,0x3f0e3f6d,0x3f713f35,0xbf7dbf35,0xbf80bf6d,0xbe793ec4,
0x3f5c3f7f,0xbedbbf62,0xbf18bf62,0xbf80bf46,0x3e163f0e,0x3f3e3e48,0x3e79be48,0xbeacbf55,0xbf2cbe95,0x3f5c3f7f,0x3f673f22,0x3f4e3e95,
0x3eac3f35,0xbe16bf35,0x3d49bec4,0xbf78bf6d,0xbf04bdc9,0x3f673ef1,0x3f4e3ef1,0xbd49bf22,0xbf7dbf55,0x3f2c3f7b,0x3f783f7b,0x3f713f0e,
0xbf3ebf75,0xbf043dc9,0x3edb3f46,0x3f183f75,0x3ef10000,0xbf220000,0xbf75bf35,0x3dc93f35,0x3f7f3f55,0xbf62bf7b,0xbf46bf7b,0xbf75bf0e,
0x3f223f6d,0x3e95bec4,0x3dc9bec4,0xbef1bf6d,0xbe953e48,0x3f7f3f55,0x3f623f0e,0x3f463e48,0x3f623f80,0xbf46bf80,0xbe95bf35,0xbf7fbf35,
0x3dc93f0e,0x3ef1be48,0x3f223e48,0xbe95bf55,0xbf46bec4,0x3f753f6d,0x3f7f3f6d,0x3f623ec4,0xbf75bf7b,0xbdc93f0e,0x3ef13f55,0x3f223f7b,
0xbe79bf35,0x3d493f35,0xbf4ebec4,0x3edb3f6d,0x3f3e3e95,0xbf7dbf22,0xbf67bf7f,0xbf5cbe95,0x3f713f7b,0xbe79bf55,0xbd49bf0e,0xbf18bf7b,
0x3e163f22,0x3f713ef1,0x3f5c3ef1,0x3f3e3dc9,0x3f783f35,0xbf80bf35,0xbf18bf6d,0xbf67bec4,0x3f2c3f75,0xbe16bf46,0x3edbbdc9,0xbf04bf75,
0xbeac3e48,0x3f783f0e,0x3f803f55,0x3f4e3e48,0xbf7dbf46,0x3eac3f62,0x3f043f62,0x3f2c3f7f,0x3f353f80,0x3f0e3f80,0x3f353f80,0xbf550000,
0xbf350000,0xbf7bbec4,0xbf350000,0xbe48bf6d,0xbf35bf80,0x3e48bf35,0xbf35bf80,0x3f7b3f35,0x3f350000,0x3f553f6d,0x3f350000,0xbf0e3ec4,
0xbf350000,0xbf550000,0xbf350000,0xbf0ebf80,0xbf35bf80,0xbe48bf6d,0xbf35bf80,0x3f7b3ec4,0x3f350000,0x3f7b3f35,0x3f350000,0xbe483f35,
0x3f353f80,0xbf0e3ec4,0x3f353f80,0xbf55bf6d,0x3f2c3f80,0x3f043f80,0x3eac3f6d,0xbf7dbec4,0xbf4ebdc9,0xbf80bef1,0xbf78bef1,0x3eacbf22,
0xbf04bf7b,0x3edbbf0e,0xbe16bf55,0x3f2c3f7b,0x3f673e95,0x3f183f7f,0x3f803f22,0xbf78be95,0xbf3e0000,0xbf5c0000,0xbf71bec4,0xbe16bf6d,
0xbf18bf7f,0xbd49bf62,0xbe79bf62,0x3f713f46,0x3f5c3e48,0x3f673f55,0x3f7d3f0e,0xbf3e3e48,0x3edb3f75,0xbf4e3dc9,0x3d493f46,0xbe79bf75,
0x3f223f80,0x3ef13f80,0xbdc93f35,0xbf75bf35,0xbf62be48,0xbf7fbf0e,0xbf75bf55,0x3f46be48,0xbe95bf6d,0x3f22bec4,0x3ef1bec4,0x3dc93f6d,
0x3f7f3f0e,0x3e953f7b,0x3f463f7b,0xbf62bf55,0xbf460000,0xbf620000,0xbf7fbf35,0x3e95bf35,0xbef1bf7b,0x3dc9bf55,0x3e95bf0e,0x3f223f7b,
0x3f753ec4,0x3f463f6d,0x3f623f6d,0xbf7fbec4,0x3dc93f55,0xbf75be48,0xbf223e48,0x3ef1bf0e,0x3f183f80,0x3edb3f80,0xbf043ec4,0xbf3ebf6d,
0xbf71be95,0xbf78bf22,0xbf2cbf7f,0x3f7d3e95,0xbd49bf55,0x3f4ebe48,0x3f673e48,0xbf043f0e,0x3f783f46,0xbd493f62,0x3e163f62,0xbeacbf7f,
0xbf4e0000,0xbf670000,0xbf5cbf6d,0x3f2cbec4,0xbeacbf75,0x3e79bf46,0x3f3ebdc9,0x3e163f75,0x3f803f0e,0x3f183f7b,0x3edb3f7b,0xbf5cbf55,
0xbe793f22,0xbf80bef1,0xbf7dbef1,0x3f713dc9,0x3f353f80,0xbf0ebf80,0x3f353f80,0x3f550000,0xbf350000,0x3f7b3ec4,0xbf350000,0x3e483f6d,
0xbf35bf80,0xbe483f35,0xbf35bf80,0xbf7bbf35,0x3f350000,0xbf55bf6d,0x3f350000,0x3f0ebec4,0xbf350000,0x3f550000,0xbf350000,0x3f0e3f80,
0xbf35bf80,0x3e483f6d,0xbf35bf80,0xbf7bbec4,0x3f350000,0xbf7bbf35,0x3f350000,0x3e48bf35,0x3f353f80,0x3f0ebec4,0x3f353f80,0x3f553f6d,
0xbd493f35,0x3e79bf35,0xbedb3ec4,0x3f4e3f6d,0xbf7dbf46,0x3f3e3f75,0xbf5cbf75,0xbf67bdc9,0x3e79bf0e,0xbf71be48,0x3f18be48,0x3d49bf55,
0x3f713f62,0x3e16bf46,0x3f3e3f7f,0x3f5c3f62,0xbf80bf35,0x3f783f35,0xbf67bf6d,0xbf183ec4,0x3e16bf22,0xbf2c3e95,0x3f04be95,0xbedbbf7f,
0x3f783f55,0xbeacbf7b,0x3f4e3f7b,0x3f803f0e,0xbeac3ef1,0x3f7d3f22,0xbf2c3dc9,0xbf043ef1,0xbf460000,0x3f620000,0xbf7fbf35,0xbe953f35,
0xbef1bf7b,0xbdc93f55,0x3e95bf0e,0xbf22bf7b,0x3f753ec4,0xbf46bf6d,0x3f623f6d,0x3f7f3ec4,0x3dc93f55,0x3f753e48,0xbf223e48,0xbef13f0e,
0xbf22bf80,0x3ef13f80,0x3dc9bf35,0xbf75bf35,0x3f623e48,0xbf7fbf0e,0x3f753f55,0x3f46be48,0x3e953f6d,0x3f22bec4,0xbef13ec4,0x3dc93f6d,
0xbf7fbf0e,0x3e953f7b,0xbf46bf7b,0xbf62bf55,0xbf7dbf35,0x3f713f35,0xbe79bf6d,0xbf80bec4,0x3edbbef1,0xbf5c3dc9,0x3f803f22,0x3f18bef1,
0x3f3e3f7b,0x3e16bf55,0xbeac3f0e,0x3e793f7b,0xbf5cbdc9,0x3f2c3f75,0xbf4ebf75,0xbf67bf46,0x3e16bf35,0xbeac3f35,0x3f783ec4,0xbd49bf6d,
0x3f673f62,0xbf04bf7f,0xbd493f46,0x3f4e3f62,0xbf2c3e48,0x3f7d3f0e,0xbf71bf55,0xbf78be48,0xbf04bf7f,0xbf3e3e95,0x3f18be95,0x3edbbf22,
0x3f353f80,0x3f0e3f80,0x3f353f80,0xbf550000,0xbf350000,0xbf7bbec4,0xbf350000,0xbe48bf6d,0xbf35bf80,0x3e48bf35,0xbf35bf80,0x3f7b3f35,
0x3f350000,0x3f553f6d,0x3f350000,0xbf0e3ec4,0xbf350000,0xbf550000,0xbf350000,0xbf0ebf80,0xbf35bf80,0xbe48bf6d,0xbf35bf80,0x3f7b3ec4,
0x3f350000,0x3f7b3f35,0x3f350000,0xbe483f35,0x3f353f80,0xbf0e3ec4,0x3f353f80,0xbf55bf6d,0xbf3e0000,0xbf5c0000,0xbf71bec4,0xbe16bf6d,
0xbf18bf7f,0xbd49bf62,0xbe79bf62,0x3f713f46,0x3f5c3e48,0x3f673f55,0x3f7d3f0e,0xbf3e3e48,0x3edb3f75,0xbf4e3dc9,0x3d493f46,0xbe79bf75,
0xbf2cbf80,0xbf04bf80,0xbeacbf6d,0x3f7d3ec4,0x3f4e3dc9,0x3f803ef1,0x3f783ef1,0xbeac3f22,0x3f043f7b,0xbedb3f0e,0x3e163f55,0xbf2cbf7b,
0xbf67be95,0xbf18bf7f,0xbf80bf22,0x3f783e95,0xbf22bf80,0xbef1bf80,0x3dc9bf35,0x3f753f35,0x3f623e48,0x3f7f3f0e,0x3f753f55,0xbf463e48,
0x3e953f6d,0xbf223ec4,0xbef13ec4,0xbdc9bf6d,0xbf7fbf0e,0xbe95bf7b,0xbf46bf7b,0x3f623f55,0x3f460000,0x3f620000,0x3f7f3f35,0xbe953f35,
0x3ef13f7b,0xbdc93f55,0xbe953f0e,0xbf22bf7b,0xbf75bec4,0xbf46bf6d,0xbf62bf6d,0x3f7f3ec4,0xbdc9bf55,0x3f753e48,0x3f22be48,0xbef13f0e,
0x3f4e0000,0x3f670000,0x3f5c3f6d,0xbf2c3ec4,0x3eac3f75,0xbe793f46,0xbf3e3dc9,0xbe16bf75,0xbf80bf0e,0xbf18bf7b,0xbedbbf7b,0x3f5c3f55,
0x3e79bf22,0x3f803ef1,0x3f7d3ef1,0xbf71bdc9,0x3f183f80,0x3edb3f80,0xbf043ec4,0xbf3ebf6d,0xbf71be95,0xbf78bf22,0xbf2cbf7f,0x3f7d3e95,
0xbd49bf55,0x3f4ebe48,0x3f673e48,0xbf043f0e,0x3f783f46,0xbd493f62,0x3e163f62,0xbeacbf7f,0x3f353f80,0xbf0ebf80,0x3f353f80,0x3f550000,
0xbf350000,0x3f7b3ec4,0xbf350000,0x3e483f6d,0xbf35bf80,0xbe483f35,0xbf35bf80,0xbf7bbf35,0x3f350000,0xbf55bf6d,0x3f350000,0x3f0ebec4,
0xbf350000,0x3f550000,0xbf350000,0x3f0e3f80,0xbf35bf80,0x3e483f6d,0xbf35bf80,0xbf7bbec4,0x3f350000,0xbf7bbf35,0x3f350000,0x3e48bf35,
0x3f353f80,0x3f0ebec4,0x3f353f80,0x3f553f6d,0xbf80bf35,0x3f783f35,0xbf67bf6d,0xbf183ec4,0x3e16bf22,0xbf2c3e95,0x3f04be95,0xbedbbf7f,
0x3f783f55,0xbeacbf7b,0x3f4e3f7b,0x3f803f0e,0xbeac3ef1,0x3f7d3f22,0xbf2c3dc9,0xbf043ef1,0x3d49bf35,0xbe793f35,0x3edbbec4,0xbf4ebf6d,
0x3f7d3f46,0xbf3ebf75,0x3f5c3f75,0x3f673dc9,0xbe793f0e,0x3f713e48,0xbf183e48,0xbd493f55,0xbf71bf62,0xbe163f46,0xbf3ebf7f,0xbf5cbf62,
0x3f460000,0xbf620000,0x3f7f3f35,0x3e95bf35,0x3ef13f7b,0x3dc9bf55,0xbe953f0e,0x3f223f7b,0xbf75bec4,0x3f463f6d,0xbf62bf6d,0xbf7fbec4,
0xbdc9bf55,0xbf75be48,0x3f22be48,0x3ef1bf0e,0x3f223f80,0xbef1bf80,0xbdc93f35,0x3f753f35,0xbf62be48,0x3f7f3f0e,0xbf75bf55,0xbf463e48,
0xbe95bf6d,0xbf223ec4,0x3ef1bec4,0xbdc9bf6d,0x3f7f3f0e,0xbe95bf7b,0x3f463f7b,0x3f623f55,0xbe163f35,0x3eacbf35,0xbf78bec4,0x3d493f6d,
0xbf67bf62,0x3f043f7f,0x3d49bf46,0xbf4ebf62,0x3f2cbe48,0xbf7dbf0e,0x3f713f55,0x3f783e48,0x3f043f7f,0x3f3ebe95,0xbf183e95,0xbedb3f22,
0xbf7dbf35,0x3f713f35,0xbe79bf6d,0xbf80bec4,0x3edbbef1,0xbf5c3dc9,0x3f803f22,0x3f18bef1,0x3f3e3f7b,0x3e16bf55,0xbeac3f0e,0x3e793f7b,
0xbf5cbdc9,0x3f2c3f75,0xbf4ebf75,0xbf67bf46,0x3f353f80,0x3f0e3f80,0x3f353f80,0xbf550000,0xbf350000,0xbf7bbec4,0xbf350000,0xbe48bf6d,
0xbf35bf80,0x3e48bf35,0xbf35bf80,0x3f7b3f35,0x3f350000,0x3f553f6d,0x3f350000,0xbf0e3ec4,0xbf350000,0xbf550000,0xbf350000,0xbf0ebf80,
0xbf35bf80,0xbe48bf6d,0xbf35bf80,0x3f7b3ec4,0x3f350000,0x3f7b3f35,0x3f350000,0xbe483f35,0x3f353f80,0xbf0e3ec4,0x3f353f80,0xbf55bf6d,
0xbf2cbf80,0xbf04bf80,0xbeacbf6d,0x3f7d3ec4,0x3f4e3dc9,0x3f803ef1,0x3f783ef1,0xbeac3f22,0x3f043f7b,0xbedb3f0e,0x3e163f55,0xbf2cbf7b,
0xbf67be95,0xbf18bf7f,0xbf80bf22,0x3f783e95,0x3f3e0000,0x3f5c0000,0x3f713ec4,0x3e163f6d,0x3f183f7f,0x3d493f62,0x3e793f62,0xbf71bf46,
0xbf5cbe48,0xbf67bf55,0xbf7dbf0e,0x3f3ebe48,0xbedbbf75,0x3f4ebdc9,0xbd49bf46,0x3e793f75,0x3f223f80,0x3ef13f80,0xbdc93f35,0xbf75bf35,
0xbf62be48,0xbf7fbf0e,0xbf75bf55,0x3f46be48,0xbe95bf6d,0x3f22bec4,0x3ef1bec4,0x3dc93f6d,0x3f7f3f0e,0x3e953f7b,0x3f463f7b,0xbf62bf55,
0xbf460000,0xbf620000,0xbf7fbf35,0x3e95bf35,0xbef1bf7b,0x3dc9bf55,0x3e95bf0e,0x3f223f7b,0x3f753ec4,0x3f463f6d,0x3f623f6d,0xbf7fbec4,
0x3dc93f55,0xbf75be48,0xbf223e48,0x3ef1bf0e,0xbf18bf80,0xbedbbf80,0x3f04bec4,0x3f3e3f6d,0x3f713e95,0x3f783f22,0x3f2c3f7f,0xbf7dbe95,
0x3d493f55,0xbf4e3e48,0xbf67be48,0x3f04bf0e,0xbf78bf46,0x3d49bf62,0xbe16bf62,0x3eac3f7f,0x3f4e0000,0x3f670000,0x3f5c3f6d,0xbf2c3ec4,
0x3eac3f75,0xbe793f46,0xbf3e3dc9,0xbe16bf75,0xbf80bf0e,0xbf18bf7b,0xbedbbf7b,0x3f5c3f55,0x3e79bf22,0x3f803ef1,0x3f7d3ef1,0xbf71bdc9,
0x3f353f80,0xbf0ebf80,0x3f353f80,0x3f550000,0xbf350000,0x3f7b3ec4,0xbf350000,0x3e483f6d,0xbf35bf80,0xbe483f35,0xbf35bf80,0xbf7bbf35,
0x3f350000,0xbf55bf6d,0x3f350000,0x3f0ebec4,0xbf350000,0x3f550000,0xbf350000,0x3f0e3f80,0xbf35bf80,0x3e483f6d,0xbf35bf80,0xbf7bbec4,
0x3f350000,0xbf7bbf35,0x3f350000,0x3e48bf35,0x3f353f80,0x3f0ebec4,0x3f353f80,0x3f553f6d,0x3d49bf35,0xbe793f35,0x3edbbec4,0xbf4ebf6d,
0x3f7d3f46,0xbf3ebf75,0x3f5c3f75,0x3f673dc9,0xbe793f0e,0x3f713e48,0xbf183e48,0xbd493f55,0xbf71bf62,0xbe163f46,0xbf3ebf7f,0xbf5cbf62,
0x3f803f35,0xbf78bf35,0x3f673f6d,0x3f18bec4,0xbe163f22,0x3f2cbe95,0xbf043e95,0x3edb3f7f,0xbf78bf55,0x3eac3f7b,0xbf4ebf7b,0xbf80bf0e,
0x3eacbef1,0xbf7dbf22,0x3f2cbdc9,0x3f04bef1,0xbf460000,0x3f620000,0xbf7fbf35,0xbe953f35,0xbef1bf7b,0xbdc93f55,0x3e95bf0e,0xbf22bf7b,
0x3f753ec4,0xbf46bf6d,0x3f623f6d,0x3f7f3ec4,0x3dc93f55,0x3f753e48,0xbf223e48,0xbef13f0e,0xbf22bf80,0x3ef13f80,0x3dc9bf35,0xbf75bf35,
0x3f623e48,0xbf7fbf0e,0x3f753f55,0x3f46be48,0x3e953f6d,0x3f22bec4,0xbef13ec4,0x3dc93f6d,0xbf7fbf0e,0x3e953f7b,0xbf46bf7b,0xbf62bf55,
0x3f7d3f35,0xbf71bf35,0x3e793f6d,0x3f803ec4,0xbedb3ef1,0x3f5cbdc9,0xbf80bf22,0xbf183ef1,0xbf3ebf7b,0xbe163f55,0x3eacbf0e,0xbe79bf7b,
0x3f5c3dc9,0xbf2cbf75,0x3f4e3f75,0x3f673f46,0xbe163f35,0x3eacbf35,0xbf78bec4,0x3d493f6d,0xbf67bf62,0x3f043f7f,0x3d49bf46,0xbf4ebf62,
0x3f2cbe48,0xbf7dbf0e,0x3f713f55,0x3f783e48,0x3f043f7f,0x3f3ebe95,0xbf183e95,0xbedb3f22,0x3f353f80,0x3f0e3f80,0x3f353f80,0xbf550000,
0xbf350000,0xbf7bbec4,0xbf350000,0xbe48bf6d,0xbf35bf80,0x3e48bf35,0xbf35bf80,0x3f7b3f35,0x3f350000,0x3f553f6d,0x3f350000,0xbf0e3ec4,
0xbf350000,0xbf550000,0xbf350000,0xbf0ebf80,0xbf35bf80,0xbe48bf6d,0xbf35bf80,0x3f7b3ec4,0x3f350000,0x3f7b3f35,0x3f350000,0xbe483f35,
0x3f353f80,0xbf0e3ec4,0x3f353f80,0xbf55bf6d,0x3f3e0000,0x3f5c0000,0x3f713ec4,0x3e163f6d,0x3f183f7f,0x3d493f62,0x3e793f62,0xbf71bf46,
0xbf5cbe48,0xbf67bf55,0xbf7dbf0e,0x3f3ebe48,0xbedbbf75,0x3f4ebdc9,0xbd49bf46,0x3e793f75,0x3f2c3f80,0x3f043f80,0x3eac3f6d,0xbf7dbec4,
0xbf4ebdc9,0xbf80bef1,0xbf78bef1,0x3eacbf22,0xbf04bf7b,0x3edbbf0e,0xbe16bf55,0x3f2c3f7b,0x3f673e95,0x3f183f7f,0x3f803f22,0xbf78be95,
0xbf22bf80,0xbef1bf80,0x3dc9bf35,0x3f753f35,0x3f623e48,0x3f7f3f0e,0x3f753f55,0xbf463e48,0x3e953f6d,0xbf223ec4,0xbef13ec4,0xbdc9bf6d,
0xbf7fbf0e,0xbe95bf7b,0xbf46bf7b,0x3f623f55,0x3f460000,0x3f620000,0x3f7f3f35,0xbe953f35,0x3ef13f7b,0xbdc93f55,0xbe953f0e,0xbf22bf7b,
0xbf75bec4,0xbf46bf6d,0xbf62bf6d,0x3f7f3ec4,0xbdc9bf55,0x3f753e48,0x3f22be48,0xbef13f0e,0xbf4e0000,0xbf670000,0xbf5cbf6d,0x3f2cbec4,
0xbeacbf75,0x3e79bf46,0x3f3ebdc9,0x3e163f75,0x3f803f0e,0x3f183f7b,0x3edb3f7b,0xbf5cbf55,0xbe793f22,0xbf80bef1,0xbf7dbef1,0x3f713dc9,
0xbf18bf80,0xbedbbf80,0x3f04bec4,0x3f3e3f6d,0x3f713e95,0x3f783f22,0x3f2c3f7f,0xbf7dbe95,0x3d493f55,0xbf4e3e48,0xbf67be48,0x3f04bf0e,
0xbf78bf46,0x3d49bf62,0xbe16bf62,0x3eac3f7f,0x3f353f80,0xbf0ebf80,0x3f353f80,0x3f550000,0xbf350000,0x3f7b3ec4,0xbf350000,0x3e483f6d,
0xbf35bf80,0xbe483f35,0xbf35bf80,0xbf7bbf35,0x3f350000,0xbf55bf6d,0x3f350000,0x3f0ebec4,0xbf350000,0x3f550000,0xbf350000,0x3f0e3f80,
0xbf35bf80,0x3e483f6d,0xbf35bf80,0xbf7bbec4,0x3f350000,0xbf7bbf35,0x3f350000,0x3e48bf35,0x3f353f80,0x3f0ebec4,0x3f353f80,0x3f553f6d,
0x3f803f35,0xbf78bf35,0x3f673f6d,0x3f18bec4,0xbe163f22,0x3f2cbe95,0xbf043e95,0x3edb3f7f,0xbf78bf55,0x3eac3f7b,0xbf4ebf7b,0xbf80bf0e,
0x3eacbef1,0xbf7dbf22,0x3f2cbdc9,0x3f04bef1,0xbd493f35,0x3e79bf35,0xbedb3ec4,0x3f4e3f6d,0xbf7dbf46,0x3f3e3f75,0xbf5cbf75,0xbf67bdc9,
0x3e79bf0e,0xbf71be48,0x3f18be48,0x3d49bf55,0x3f713f62,0x3e16bf46,0x3f3e3f7f,0x3f5c3f62,0x3f460000,0xbf620000,0x3f7f3f35,0x3e95bf35,
0x3ef13f7b,0x3dc9bf55,0xbe953f0e,0x3f223f7b,0xbf75bec4,0x3f463f6d,0xbf62bf6d,0xbf7fbec4,0xbdc9bf55,0xbf75be48,0x3f22be48,0x3ef1bf0e,
0x3f223f80,0xbef1bf80,0xbdc93f35,0x3f753f35,0xbf62be48,0x3f7f3f0e,0xbf75bf55,0xbf463e48,0xbe95bf6d,0xbf223ec4,0x3ef1bec4,0xbdc9bf6d,
0x3f7f3f0e,0xbe95bf7b,0x3f463f7b,0x3f623f55,0x3e16bf35,0xbeac3f35,0x3f783ec4,0xbd49bf6d,0x3f673f62,0xbf04bf7f,0xbd493f46,0x3f4e3f62,
0xbf2c3e48,0x3f7d3f0e,0xbf71bf55,0xbf78be48,0xbf04bf7f,0xbf3e3e95,0x3f18be95,0x3edbbf22,0x3f7d3f35,0xbf71bf35,0x3e793f6d,0x3f803ec4,
0xbedb3ef1,0x3f5cbdc9,0xbf80bf22,0xbf183ef1,0xbf3ebf7b,0xbe163f55,0x3eacbf0e,0xbe79bf7b,0x3f5c3dc9,0xbf2cbf75,0x3f4e3f75,0x3f673f46,
0x3ec43f80,0x3e483f80,0xbec4bf80,0x3f7b0000,0xbf6dbf35,0xbf0ebf6d,0x3f6d3f35,0xbf553ec4,0x3f6d0000,0x3f553f35,0xbf6d0000,0x3f0ebf35,
0xbec43f35,0xbf7bbec4,0x3ec4bf35,0xbe483f6d,0xbf6d0000,0xbf7b0000,0x3f6d0000,0x3e483f80,0x3ec4bf35,0x3f55bec4,0xbec43f35,0xbf0ebf6d,
0x3ec43f80,0xbf0e3f35,0xbec4bf80,0x3f553f35,0xbf6dbf35,0x3e48bf6d,0x3f6d3f35,0xbf7bbec4,0x3eac3f80,0x3e163f80,0x3d49bf6d,0x3f783ec4,
0xbf5cbf46,0xbedbbf75,0x3f183f75,0xbf80bdc9,0x3f7d3e48,0x3f2c3f55,0xbf78bf0e,0x3f71be48,0xbf2c3ef1,0xbf5cbf22,0x3f67bdc9,0xbf4e3ef1,
0xbf710000,0xbf7d0000,0x3f803ec4,0xbe793f6d,0x3f04bf22,0x3f67be95,0xbf4e3e95,0xbd49bf7f,0x3e163f7b,0xbf3e3f0e,0x3e79bf55,0x3eac3f7b,
0xbf3ebf62,0x3f04bf46,0x3edb3f7f,0xbf18bf62,0x3e953f80,0x3dc93f80,0x3ef1bf35,0x3f463f35,0xbf46bf55,0xbe95bf7b,0x3dc93f7b,0xbf62bf0e,
0x3f7f3ec4,0x3ef13f6d,0xbf22bf6d,0x3f753ec4,0xbf623e48,0xbf22bf55,0x3f753f0e,0xbf7fbe48,0xbf750000,0xbf7f0000,0x3f623f35,0xbf223f35,
0x3f22bf0e,0x3f75be48,0xbf7fbe48,0x3ef1bf55,0xbdc93f6d,0xbf623ec4,0x3f46bec4,0xbe953f6d,0xbef1bf7b,0x3f46bf0e,0xbe953f55,0x3dc9bf7b,
0x3e793f80,0x3d493f80,0x3f4ebec4,0x3edb3f6d,0xbf2cbf62,0xbe16bf7f,0xbedb3f46,0xbf04bf62,0x3f713f0e,0x3e793f7b,0xbd49bf7b,0x3f183f55,
0xbf7dbdc9,0xbeacbf75,0x3f043f75,0xbf2cbf46,0xbf780000,0xbf800000,0x3f183f6d,0xbf673ec4,0x3f3ebef1,0x3f7dbdc9,0xbf67bf22,0x3f5cbef1,
0xbeac3f55,0xbf783e48,0x3f803e48,0xbf4e3f0e,0xbe16bf7f,0x3f71be95,0xbf5c3e95,0x3f3ebf22,0x3ec43f80,0xbe48bf80,0xbec4bf80,0xbf7b0000,
0xbf6dbf35,0x3f0e3f6d,0x3f6d3f35,0x3f55bec4,0x3f6d0000,0xbf55bf35,0xbf6d0000,0xbf0e3f35,0xbec43f35,0x3f7b3ec4,0x3ec4bf35,0x3e48bf6d,
0xbf6d0000,0x3f7b0000,0x3f6d0000,0xbe48bf80,0x3ec4bf35,0xbf553ec4,0xbec43f35,0x3f0e3f6d,0x3ec43f80,0x3f0ebf35,0xbec4bf80,0xbf55bf35,
0xbf6dbf35,0xbe483f6d,0x3f6d3f35,0x3f7b3ec4,0xbedb3f35,0x3f18bf35,0x3f3ebec4,0xbf04bf6d,0xbe79bf7f,0xbeac3f62,0xbe163f62,0x3f3e3f46,
0x3f4e3f55,0x3d49bf7b,0xbf04bf7b,0xbf67bf0e,0xbf80be95,0x3e793f7f,0x3f713f22,0x3f7d3e95,0xbf67bf35,0x3f4e3f35,0x3f2c3f6d,0x3f5cbec4,
0x3f783dc9,0xbf71bef1,0xbf7dbef1,0xbf2c3f22,0xbf183f0e,0x3f803e48,0x3f5cbe48,0x3edbbf55,0xbd49bf75,0xbf783dc9,0xbeac3f46,0xbe163f75,
0xbf750000,0x3f7f0000,0x3f623f35,0x3f22bf35,0x3f22bf0e,0xbf753e48,0xbf7fbe48,0xbef13f55,0xbdc93f6d,0x3f62bec4,0x3f46bec4,0x3e95bf6d,
0xbef1bf7b,0xbf463f0e,0xbe953f55,0xbdc93f7b,0xbe95bf80,0x3dc93f80,0xbef13f35,0x3f463f35,0x3f463f55,0xbe95bf7b,0xbdc9bf7b,0xbf62bf0e,
0xbf7fbec4,0x3ef13f6d,0x3f223f6d,0x3f753ec4,0x3f62be48,0xbf22bf55,0xbf75bf0e,0xbf7fbe48,0xbf5cbf35,0x3f3e3f35,0xbe163f6d,0x3f713ec4,
0x3f803e95,0xbf4ebf22,0xbeacbf7f,0xbf78be95,0xbf673e48,0x3f5c3f0e,0x3f3e3f55,0x3f7d3e48,0x3f18bf22,0xbf67bef1,0xbf78bef1,0xbf80bdc9,
0x3f04bf35,0xbf2c3f35,0xbf7dbec4,0xbeac3f6d,0xbd493f75,0x3f18bf46,0x3f71bdc9,0x3e79bf75,0xbedbbf7b,0xbf043f55,0xbf2c3f0e,0xbe163f7b,
0x3f4e3f46,0x3edbbf62,0x3e79bf62,0x3d49bf7f,0x3ec43f80,0x3e483f80,0xbec4bf80,0x3f7b0000,0xbf6dbf35,0xbf0ebf6d,0x3f6d3f35,0xbf553ec4,
0x3f6d0000,0x3f553f35,0xbf6d0000,0x3f0ebf35,0xbec43f35,0xbf7bbec4,0x3ec4bf35,0xbe483f6d,0xbf6d0000,0xbf7b0000,0x3f6d0000,0x3e483f80,
0x3ec4bf35,0x3f55bec4,0xbec43f35,0xbf0ebf6d,0x3ec43f80,0xbf0e3f35,0xbec4bf80,0x3f553f35,0xbf6dbf35,0x3e48bf6d,0x3f6d3f35,0xbf7bbec4,
0xbf710000,0xbf7d0000,0x3f803ec4,0xbe793f6d,0x3f04bf22,0x3f67be95,0xbf4e3e95,0xbd49bf7f,0x3e163f7b,0xbf3e3f0e,0x3e79bf55,0x3eac3f7b,
0xbf3ebf62,0x3f04bf46,0x3edb3f7f,0xbf18bf62,0xbeacbf80,0xbe16bf80,0xbd493f6d,0xbf78bec4,0x3f5c3f46,0x3edb3f75,0xbf18bf75,0x3f803dc9,
0xbf7dbe48,0xbf2cbf55,0x3f783f0e,0xbf713e48,0x3f2cbef1,0x3f5c3f22,0xbf673dc9,0x3f4ebef1,0xbe95bf80,0xbdc9bf80,0xbef13f35,0xbf46bf35,
0x3f463f55,0x3e953f7b,0xbdc9bf7b,0x3f623f0e,0xbf7fbec4,0xbef1bf6d,0x3f223f6d,0xbf75bec4,0x3f62be48,0x3f223f55,0xbf75bf0e,0x3f7f3e48,
0x3f750000,0x3f7f0000,0xbf62bf35,0x3f22bf35,0xbf223f0e,0xbf753e48,0x3f7f3e48,0xbef13f55,0x3dc9bf6d,0x3f62bec4,0xbf463ec4,0x3e95bf6d,
0x3ef13f7b,0xbf463f0e,0x3e95bf55,0xbdc93f7b,0x3f780000,0x3f800000,0xbf18bf6d,0x3f67bec4,0xbf3e3ef1,0xbf7d3dc9,0x3f673f22,0xbf5c3ef1,
0x3eacbf55,0x3f78be48,0xbf80be48,0x3f4ebf0e,0x3e163f7f,0xbf713e95,0x3f5cbe95,0xbf3e3f22,0x3e793f80,0x3d493f80,0x3f4ebec4,0x3edb3f6d,
0xbf2cbf62,0xbe16bf7f,0xbedb3f46,0xbf04bf62,0x3f713f0e,0x3e793f7b,0xbd49bf7b,0x3f183f55,0xbf7dbdc9,0xbeacbf75,0x3f043f75,0xbf2cbf46,
0x3ec43f80,0xbe48bf80,0xbec4bf80,0xbf7b0000,0xbf6dbf35,0x3f0e3f6d,0x3f6d3f35,0x3f55bec4,0x3f6d0000,0xbf55bf35,0xbf6d0000,0xbf0e3f35,
0xbec43f35,0x3f7b3ec4,0x3ec4bf35,0x3e48bf6d,0xbf6d0000,0x3f7b0000,0x3f6d0000,0xbe48bf80,0x3ec4bf35,0xbf553ec4,0xbec43f35,0x3f0e3f6d,
0x3ec43f80,0x3f0ebf35,0xbec4bf80,0xbf55bf35,0xbf6dbf35,0xbe483f6d,0x3f6d3f35,0x3f7b3ec4,0xbf67bf35,0x3f4e3f35,0x3f2c3f6d,0x3f5cbec4,
0x3f783dc9,0xbf71bef1,0xbf7dbef1,0xbf2c3f22,0xbf183f0e,0x3f803e48,0x3f5cbe48,0x3edbbf55,0xbd49bf75,0xbf783dc9,0xbeac3f46,0xbe163f75,
0x3edbbf35,0xbf183f35,0xbf3e3ec4,0x3f043f6d,0x3e793f7f,0x3eacbf62,0x3e16bf62,0xbf3ebf46,0xbf4ebf55,0xbd493f7b,0x3f043f7b,0x3f673f0e,
0x3f803e95,0xbe79bf7f,0xbf71bf22,0xbf7dbe95,0x3f750000,0xbf7f0000,0xbf62bf35,0xbf223f35,0xbf223f0e,0x3f75be48,0x3f7f3e48,0x3ef1bf55,
0x3dc9bf6d,0xbf623ec4,0xbf463ec4,0xbe953f6d,0x3ef13f7b,0x3f46bf0e,0x3e95bf55,0x3dc9bf7b,0x3e953f80,0xbdc9bf80,0x3ef1bf35,0xbf46bf35,
0xbf46bf55,0x3e953f7b,0x3dc93f7b,0x3f623f0e,0x3f7f3ec4,0xbef1bf6d,0xbf22bf6d,0xbf75bec4,0xbf623e48,0x3f223f55,0x3f753f0e,0x3f7f3e48,
0xbf043f35,0x3f2cbf35,0x3f7d3ec4,0x3eacbf6d,0x3d49bf75,0xbf183f46,0xbf713dc9,0xbe793f75,0x3edb3f7b,0x3f04bf55,0x3f2cbf0e,0x3e16bf7b,
0xbf4ebf46,0xbedb3f62,0xbe793f62,0xbd493f7f,0xbf5cbf35,0x3f3e3f35,0xbe163f6d,0x3f713ec4,0x3f803e95,0xbf4ebf22,0xbeacbf7f,0xbf78be95,
0xbf673e48,0x3f5c3f0e,0x3f3e3f55,0x3f7d3e48,0x3f18bf22,0xbf67bef1,0xbf78bef1,0xbf80bdc9,0x3ec43f80,0x3e483f80,0xbec4bf80,0x3f7b0000,
0xbf6dbf35,0xbf0ebf6d,0x3f6d3f35,0xbf553ec4,0x3f6d0000,0x3f553f35,0xbf6d0000,0x3f0ebf35,0xbec43f35,0xbf7bbec4,0x3ec4bf35,0xbe483f6d,
0xbf6d0000,0xbf7b0000,0x3f6d0000,0x3e483f80,0x3ec4bf35,0x3f55bec4,0xbec43f35,0xbf0ebf6d,0x3ec43f80,0xbf0e3f35,0xbec4bf80,0x3f553f35,
0xbf6dbf35,0x3e48bf6d,0x3f6d3f35,0xbf7bbec4,0xbeacbf80,0xbe16bf80,0xbd493f6d,0xbf78bec4,0x3f5c3f46,0x3edb3f75,0xbf18bf75,0x3f803dc9,
0xbf7dbe48,0xbf2cbf55,0x3f783f0e,0xbf713e48,0x3f2cbef1,0x3f5c3f22,0xbf673dc9,0x3f4ebef1,0x3f710000,0x3f7d0000,0xbf80bec4,0x3e79bf6d,
0xbf043f22,0xbf673e95,0x3f4ebe95,0x3d493f7f,0xbe16bf7b,0x3f3ebf0e,0xbe793f55,0xbeacbf7b,0x3f3e3f62,0xbf043f46,0xbedbbf7f,0x3f183f62,
0x3e953f80,0x3dc93f80,0x3ef1bf35,0x3f463f35,0xbf46bf55,0xbe95bf7b,0x3dc93f7b,0xbf62bf0e,0x3f7f3ec4,0x3ef13f6d,0xbf22bf6d,0x3f753ec4,
0xbf623e48,0xbf22bf55,0x3f753f0e,0xbf7fbe48,0xbf750000,0xbf7f0000,0x3f623f35,0xbf223f35,0x3f22bf0e,0x3f75be48,0xbf7fbe48,0x3ef1bf55,
0xbdc93f6d,0xbf623ec4,0x3f46bec4,0xbe953f6d,0xbef1bf7b,0x3f46bf0e,0xbe953f55,0x3dc9bf7b,0xbe79bf80,0xbd49bf80,0xbf4e3ec4,0xbedbbf6d,
0x3f2c3f62,0x3e163f7f,0x3edbbf46,0x3f043f62,0xbf71bf0e,0xbe79bf7b,0x3d493f7b,0xbf18bf55,0x3f7d3dc9,0x3eac3f75,0xbf04bf75,0x3f2c3f46,
0x3f780000,0x3f800000,0xbf18bf6d,0x3f67bec4,0xbf3e3ef1,0xbf7d3dc9,0x3f673f22,0xbf5c3ef1,0x3eacbf55,0x3f78be48,0xbf80be48,0x3f4ebf0e,
0x3e163f7f,0xbf713e95,0x3f5cbe95,0xbf3e3f22,0x3ec43f80,0xbe48bf80,0xbec4bf80,0xbf7b0000,0xbf6dbf35,0x3f0e3f6d,0x3f6d3f35,0x3f55bec4,
0x3f6d0000,0xbf55bf35,0xbf6d0000,0xbf0e3f35,0xbec43f35,0x3f7b3ec4,0x3ec4bf35,0x3e48bf6d,0xbf6d0000,0x3f7b0000,0x3f6d0000,0xbe48bf80,
0x3ec4bf35,0xbf553ec4,0xbec43f35,0x3f0e3f6d,0x3ec43f80,0x3f0ebf35,0xbec4bf80,0xbf55bf35,0xbf6dbf35,0xbe483f6d,0x3f6d3f35,0x3f7b3ec4,
0x3edbbf35,0xbf183f35,0xbf3e3ec4,0x3f043f6d,0x3e793f7f,0x3eacbf62,0x3e16bf62,0xbf3ebf46,0xbf4ebf55,0xbd493f7b,0x3f043f7b,0x3f673f0e,
0x3f803e95,0xbe79bf7f,0xbf71bf22,0xbf7dbe95,0x3f673f35,0xbf4ebf35,0xbf2cbf6d,0xbf5c3ec4,0xbf78bdc9,0x3f713ef1,0x3f7d3ef1,0x3f2cbf22,
0x3f18bf0e,0xbf80be48,0xbf5c3e48,0xbedb3f55,0x3d493f75,0x3f78bdc9,0x3eacbf46,0x3e16bf75,0xbf750000,0x3f7f0000,0x3f623f35,0x3f22bf35,
0x3f22bf0e,0xbf753e48,0xbf7fbe48,0xbef13f55,0xbdc93f6d,0x3f62bec4,0x3f46bec4,0x3e95bf6d,0xbef1bf7b,0xbf463f0e,0xbe953f55,0xbdc93f7b,
0xbe95bf80,0x3dc93f80,0xbef13f35,0x3f463f35,0x3f463f55,0xbe95bf7b,0xbdc9bf7b,0xbf62bf0e,0xbf7fbec4,0x3ef13f6d,0x3f223f6d,0x3f753ec4,
0x3f62be48,0xbf22bf55,0xbf75bf0e,0xbf7fbe48,0x3f5c3f35,0xbf3ebf35,0x3e16bf6d,0xbf71bec4,0xbf80be95,0x3f4e3f22,0x3eac3f7f,0x3f783e95,
0x3f67be48,0xbf5cbf0e,0xbf3ebf55,0xbf7dbe48,0xbf183f22,0x3f673ef1,0x3f783ef1,0x3f803dc9,0xbf043f35,0x3f2cbf35,0x3f7d3ec4,0x3eacbf6d,
0x3d49bf75,0xbf183f46,0xbf713dc9,0xbe793f75,0x3edb3f7b,0x3f04bf55,0x3f2cbf0e,0x3e16bf7b,0xbf4ebf46,0xbedb3f62,0xbe793f62,0xbd493f7f,
0x3ec43f80,0x3e483f80,0xbec4bf80,0x3f7b0000,0xbf6dbf35,0xbf0ebf6d,0x3f6d3f35,0xbf553ec4,0x3f6d0000,0x3f553f35,0xbf6d0000,0x3f0ebf35,
0xbec43f35,0xbf7bbec4,0x3ec4bf35,0xbe483f6d,0xbf6d0000,0xbf7b0000,0x3f6d0000,0x3e483f80,0x3ec4bf35,0x3f55bec4,0xbec43f35,0xbf0ebf6d,
0x3ec43f80,0xbf0e3f35,0xbec4bf80,0x3f553f35,0xbf6dbf35,0x3e48bf6d,0x3f6d3f35,0xbf7bbec4,0x3f710000,0x3f7d0000,0xbf80bec4,0x3e79bf6d,
0xbf043f22,0xbf673e95,0x3f4ebe95,0x3d493f7f,0xbe16bf7b,0x3f3ebf0e,0xbe793f55,0xbeacbf7b,0x3f3e3f62,0xbf043f46,0xbedbbf7f,0x3f183f62,
0x3eac3f80,0x3e163f80,0x3d49bf6d,0x3f783ec4,0xbf5cbf46,0xbedbbf75,0x3f183f75,0xbf80bdc9,0x3f7d3e48,0x3f2c3f55,0xbf78bf0e,0x3f71be48,
0xbf2c3ef1,0xbf5cbf22,0x3f67bdc9,0xbf4e3ef1,0xbe95bf80,0xbdc9bf80,0xbef13f35,0xbf46bf35,0x3f463f55,0x3e953f7b,0xbdc9bf7b,0x3f623f0e,
0xbf7fbec4,0xbef1bf6d,0x3f223f6d,0xbf75bec4,0x3f62be48,0x3f223f55,0xbf75bf0e,0x3f7f3e48,0x3f750000,0x3f7f0000,0xbf62bf35,0x3f22bf35,
0xbf223f0e,0xbf753e48,0x3f7f3e48,0xbef13f55,0x3dc9bf6d,0x3f62bec4,0xbf463ec4,0x3e95bf6d,0x3ef13f7b,0xbf463f0e,0x3e95bf55,0xbdc93f7b,
0xbf780000,0xbf800000,0x3f183f6d,0xbf673ec4,0x3f3ebef1,0x3f7dbdc9,0xbf67bf22,0x3f5cbef1,0xbeac3f55,0xbf783e48,0x3f803e48,0xbf4e3f0e,
0xbe16bf7f,0x3f71be95,0xbf5c3e95,0x3f3ebf22,0xbe79bf80,0xbd49bf80,0xbf4e3ec4,0xbedbbf6d,0x3f2c3f62,0x3e163f7f,0x3edbbf46,0x3f043f62,
0xbf71bf0e,0xbe79bf7b,0x3d493f7b,0xbf18bf55,0x3f7d3dc9,0x3eac3f75,0xbf04bf75,0x3f2c3f46,0x3ec43f80,0xbe48bf80,0xbec4bf80,0xbf7b0000,
0xbf6dbf35,0x3f0e3f6d,0x3f6d3f35,0x3f55bec4,0x3f6d0000,0xbf55bf35,0xbf6d0000,0xbf0e3f35,0xbec43f35,0x3f7b3ec4,0x3ec4bf35,0x3e48bf6d,
0xbf6d0000,0x3f7b0000,0x3f6d0000,0xbe48bf80,0x3ec4bf35,0xbf553ec4,0xbec43f35,0x3f0e3f6d,0x3ec43f80,0x3f0ebf35,0xbec4bf80,0xbf55bf35,
0xbf6dbf35,0xbe483f6d,0x3f6d3f35,0x3f7b3ec4,0x3f673f35,0xbf4ebf35,0xbf2cbf6d,0xbf5c3ec4,0xbf78bdc9,0x3f713ef1,0x3f7d3ef1,0x3f2cbf22,
0x3f18bf0e,0xbf80be48,0xbf5c3e48,0xbedb3f55,0x3d493f75,0x3f78bdc9,0x3eacbf46,0x3e16bf75,0xbedb3f35,0x3f18bf35,0x3f3ebec4,0xbf04bf6d,
0xbe79bf7f,0xbeac3f62,0xbe163f62,0x3f3e3f46,0x3f4e3f55,0x3d49bf7b,0xbf04bf7b,0xbf67bf0e,0xbf80be95,0x3e793f7f,0x3f713f22,0x3f7d3e95,
0x3f750000,0xbf7f0000,0xbf62bf35,0xbf223f35,0xbf223f0e,0x3f75be48,0x3f7f3e48,0x3ef1bf55,0x3dc9bf6d,0xbf623ec4,0xbf463ec4,0xbe953f6d,
0x3ef13f7b,0x3f46bf0e,0x3e95bf55,0x3dc9bf7b,0x3e953f80,0xbdc9bf80,0x3ef1bf35,0xbf46bf35,0xbf46bf55,0x3e953f7b,0x3dc93f7b,0x3f623f0e,
0x3f7f3ec4,0xbef1bf6d,0xbf22bf6d,0xbf75bec4,0xbf623e48,0x3f223f55,0x3f753f0e,0x3f7f3e48,0x3f04bf35,0xbf2c3f35,0xbf7dbec4,0xbeac3f6d,
0xbd493f75,0x3f18bf46,0x3f71bdc9,0x3e79bf75,0xbedbbf7b,0xbf043f55,0xbf2c3f0e,0xbe163f7b,0x3f4e3f46,0x3edbbf62,0x3e79bf62,0x3d49bf7f,
0x3f5c3f35,0xbf3ebf35,0x3e16bf6d,0xbf71bec4,0xbf80be95,0x3f4e3f22,0x3eac3f7f,0x3f783e95,0x3f67be48,0xbf5cbf0e,0xbf3ebf55,0xbf7dbe48,
0xbf183f22,0x3f673ef1,0x3f783ef1,0x3f803dc9,0x3f80,0xbe483f80,0x3f80,0xbf7b0000,0xbf80,0x3f0ebf6d,0xbf80,0x3f553ec4,
0x3f80,0xbf553f35,0x3f80,0xbf0ebf35,0xbf80,0x3f7bbec4,0xbf80,0x3e483f6d,0xbf800000,0xbf7b0000,0xbf800000,0x3e48bf80,
0x3f800000,0x3f553ec4,0x3f800000,0xbf0e3f6d,0xbf800000,0xbf0ebf35,0xbf800000,0x3f55bf35,0x3f800000,0x3e483f6d,0x3f800000,0xbf7b3ec4,
0xbd493f80,0xbe793f80,0xbedb3f6d,0xbf4ebec4,0x3e16bf7f,0x3f2cbf62,0x3f04bf62,0x3edb3f46,0xbe793f7b,0xbf713f0e,0xbf183f55,0x3d49bf7b,
0x3eacbf75,0x3f7dbdc9,0x3f2cbf46,0xbf043f75,0xbf800000,0xbf780000,0xbf67bec4,0x3f18bf6d,0x3f7d3dc9,0x3f3e3ef1,0x3f5c3ef1,0xbf673f22,
0xbf78be48,0xbeacbf55,0xbf4ebf0e,0x3f80be48,0x3f713e95,0xbe163f7f,0x3f3e3f22,0xbf5cbe95,0xbdc93f80,0xbe953f80,0xbf463f35,0xbef1bf35,
0x3e95bf7b,0x3f46bf55,0x3f62bf0e,0xbdc93f7b,0xbef13f6d,0xbf7f3ec4,0xbf753ec4,0x3f22bf6d,0x3f22bf55,0x3f623e48,0x3f7fbe48,0xbf753f0e,
0xbf7f0000,0xbf750000,0xbf22bf35,0x3f62bf35,0x3f753e48,0x3f223f0e,0x3ef13f55,0xbf7f3e48,0xbf62bec4,0xbdc9bf6d,0xbe95bf6d,0x3f463ec4,
0x3f463f0e,0xbef13f7b,0x3dc93f7b,0xbe95bf55,0xbe163f80,0xbeac3f80,0xbf783ec4,0xbd49bf6d,0x3edbbf75,0x3f5cbf46,0x3f80bdc9,0xbf183f75,
0xbf2c3f55,0xbf7d3e48,0xbf71be48,0x3f78bf0e,0x3f5cbf22,0x3f2c3ef1,0x3f4e3ef1,0xbf67bdc9,0xbf7d0000,0xbf710000,0xbe79bf6d,0x3f80bec4,
0x3f673e95,0x3f043f22,0xbd493f7f,0xbf4ebe95,0xbf3ebf0e,0x3e16bf7b,0x3eacbf7b,0x3e793f55,0x3f043f46,0xbf3e3f62,0xbf183f62,0x3edbbf7f,
0x3f80,0x3e48bf80,0x3f80,0x3f7b0000,0xbf80,0xbf0e3f6d,0xbf80,0xbf55bec4,0x3f80,0x3f55bf35,0x3f80,0x3f0e3f35,
0xbf80,0xbf7b3ec4,0xbf80,0xbe48bf6d,0xbf800000,0x3f7b0000,0xbf800000,0xbe483f80,0x3f800000,0xbf55bec4,0x3f800000,0x3f0ebf6d,
0xbf800000,0x3f0e3f35,0xbf800000,0xbf553f35,0x3f800000,0xbe48bf6d,0x3f800000,0x3f7bbec4,0xbf3e3f35,0x3f5cbf35,0xbf713ec4,0x3e163f6d,
0x3f4ebf22,0xbf803e95,0x3f78be95,0x3eacbf7f,0xbf5c3f0e,0x3f673e48,0xbf7d3e48,0xbf3e3f55,0x3f67bef1,0xbf18bf22,0x3f80bdc9,0x3f78bef1,
0xbf2cbf35,0x3f043f35,0xbeacbf6d,0xbf7d3ec4,0x3f183f46,0xbd49bf75,0x3e793f75,0x3f713dc9,0xbf04bf55,0xbedb3f7b,0xbe16bf7b,0xbf2cbf0e,
0x3edb3f62,0x3f4ebf46,0x3d493f7f,0x3e793f62,0xbf7f0000,0x3f750000,0xbf22bf35,0xbf623f35,0x3f753e48,0xbf22bf0e,0x3ef13f55,0x3f7fbe48,
0xbf62bec4,0x3dc93f6d,0xbe95bf6d,0xbf46bec4,0x3f463f0e,0x3ef1bf7b,0x3dc93f7b,0x3e953f55,0x3dc9bf80,0xbe953f80,0x3f46bf35,0xbef1bf35,
0xbe953f7b,0x3f46bf55,0xbf623f0e,0xbdc93f7b,0x3ef1bf6d,0xbf7f3ec4,0x3f75bec4,0x3f22bf6d,0xbf223f55,0x3f623e48,0xbf7f3e48,0xbf753f0e,
0xbf18bf35,0x3edb3f35,0x3f04bf6d,0xbf3ebec4,0x3eac3f62,0x3e79bf7f,0xbf3e3f46,0x3e163f62,0xbd49bf7b,0xbf4e3f55,0x3f67bf0e,0x3f04bf7b,
0xbe793f7f,0x3f80be95,0xbf7d3e95,0xbf713f22,0x3f4ebf35,0xbf673f35,0x3f5c3ec4,0x3f2cbf6d,0xbf713ef1,0x3f78bdc9,0xbf2cbf22,0xbf7d3ef1,
0x3f80be48,0xbf18bf0e,0x3edb3f55,0x3f5c3e48,0xbf78bdc9,0xbd493f75,0xbe16bf75,0xbeacbf46,0x3f80,0xbe483f80,0x3f80,0xbf7b0000,
0xbf80,0x3f0ebf6d,0xbf80,0x3f553ec4,0x3f80,0xbf553f35,0x3f80,0xbf0ebf35,0xbf80,0x3f7bbec4,0xbf80,0x3e483f6d,
0xbf800000,0xbf7b0000,0xbf800000,0x3e48bf80,0x3f800000,0x3f553ec4,0x3f800000,0xbf0e3f6d,0xbf800000,0xbf0ebf35,0xbf800000,0x3f55bf35,
0x3f800000,0x3e483f6d,0x3f800000,0xbf7b3ec4,0xbf800000,0xbf780000,0xbf67bec4,0x3f18bf6d,0x3f7d3dc9,0x3f3e3ef1,0x3f5c3ef1,0xbf673f22,
0xbf78be48,0xbeacbf55,0xbf4ebf0e,0x3f80be48,0x3f713e95,0xbe163f7f,0x3f3e3f22,0xbf5cbe95,0x3d49bf80,0x3e79bf80,0x3edbbf6d,0x3f4e3ec4,
0xbe163f7f,0xbf2c3f62,0xbf043f62,0xbedbbf46,0x3e79bf7b,0x3f71bf0e,0x3f18bf55,0xbd493f7b,0xbeac3f75,0xbf7d3dc9,0xbf2c3f46,0x3f04bf75,
0x3dc9bf80,0x3e95bf80,0x3f46bf35,0x3ef13f35,0xbe953f7b,0xbf463f55,0xbf623f0e,0x3dc9bf7b,0x3ef1bf6d,0x3f7fbec4,0x3f75bec4,0xbf223f6d,
0xbf223f55,0xbf62be48,0xbf7f3e48,0x3f75bf0e,0x3f7f0000,0x3f750000,0x3f223f35,0xbf623f35,0xbf75be48,0xbf22bf0e,0xbef1bf55,0x3f7fbe48,
0x3f623ec4,0x3dc93f6d,0x3e953f6d,0xbf46bec4,0xbf46bf0e,0x3ef1bf7b,0xbdc9bf7b,0x3e953f55,0x3f7d0000,0x3f710000,0x3e793f6d,0xbf803ec4,
0xbf67be95,0xbf04bf22,0x3d49bf7f,0x3f4e3e95,0x3f3e3f0e,0xbe163f7b,0xbeac3f7b,0xbe79bf55,0xbf04bf46,0x3f3ebf62,0x3f18bf62,0xbedb3f7f,
0xbe163f80,0xbeac3f80,0xbf783ec4,0xbd49bf6d,0x3edbbf75,0x3f5cbf46,0x3f80bdc9,0xbf183f75,0xbf2c3f55,0xbf7d3e48,0xbf71be48,0x3f78bf0e,
0x3f5cbf22,0x3f2c3ef1,0x3f4e3ef1,0xbf67bdc9,0x3f80,0x3e48bf80,0x3f80,0x3f7b0000,0xbf80,0xbf0e3f6d,0xbf80,0xbf55bec4,
0x3f80,0x3f55bf35,0x3f80,0x3f0e3f35,0xbf80,0xbf7b3ec4,0xbf80,0xbe48bf6d,0xbf800000,0x3f7b0000,0xbf800000,0xbe483f80,
0x3f800000,0xbf55bec4,0x3f800000,0x3f0ebf6d,0xbf800000,0x3f0e3f35,0xbf800000,0xbf553f35,0x3f800000,0xbe48bf6d,0x3f800000,0x3f7bbec4,
0xbf2cbf35,0x3f043f35,0xbeacbf6d,0xbf7d3ec4,0x3f183f46,0xbd49bf75,0x3e793f75,0x3f713dc9,0xbf04bf55,0xbedb3f7b,0xbe16bf7b,0xbf2cbf0e,
0x3edb3f62,0x3f4ebf46,0x3d493f7f,0x3e793f62,0x3f3ebf35,0xbf5c3f35,0x3f71bec4,0xbe16bf6d,0xbf4e3f22,0x3f80be95,0xbf783e95,0xbeac3f7f,
0x3f5cbf0e,0xbf67be48,0x3f7dbe48,0x3f3ebf55,0xbf673ef1,0x3f183f22,0xbf803dc9,0xbf783ef1,0x3f7f0000,0xbf750000,0x3f223f35,0x3f62bf35,
0xbf75be48,0x3f223f0e,0xbef1bf55,0xbf7f3e48,0x3f623ec4,0xbdc9bf6d,0x3e953f6d,0x3f463ec4,0xbf46bf0e,0xbef13f7b,0xbdc9bf7b,0xbe95bf55,
0xbdc93f80,0x3e95bf80,0xbf463f35,0x3ef13f35,0x3e95bf7b,0xbf463f55,0x3f62bf0e,0x3dc9bf7b,0xbef13f6d,0x3f7fbec4,0xbf753ec4,0xbf223f6d,
0x3f22bf55,0xbf62be48,0x3f7fbe48,0x3f75bf0e,0xbf4e3f35,0x3f67bf35,0xbf5cbec4,0xbf2c3f6d,0x3f71bef1,0xbf783dc9,0x3f2c3f22,0x3f7dbef1,
0xbf803e48,0x3f183f0e,0xbedbbf55,0xbf5cbe48,0x3f783dc9,0x3d49bf75,0x3e163f75,0x3eac3f46,0xbf18bf35,0x3edb3f35,0x3f04bf6d,0xbf3ebec4,
0x3eac3f62,0x3e79bf7f,0xbf3e3f46,0x3e163f62,0xbd49bf7b,0xbf4e3f55,0x3f67bf0e,0x3f04bf7b,0xbe793f7f,0x3f80be95,0xbf7d3e95,0xbf713f22,
0x3f80,0xbe483f80,0x3f80,0xbf7b0000,0xbf80,0x3f0ebf6d,0xbf80,0x3f553ec4,0x3f80,0xbf553f35,0x3f80,0xbf0ebf35,
0xbf80,0x3f7bbec4,0xbf80,0x3e483f6d,0xbf800000,0xbf7b0000,0xbf800000,0x3e48bf80,0x3f800000,0x3f553ec4,0x3f800000,0xbf0e3f6d,
0xbf800000,0xbf0ebf35,0xbf800000,0x3f55bf35,0x3f800000,0x3e483f6d,0x3f800000,0xbf7b3ec4,0x3d49bf80,0x3e79bf80,0x3edbbf6d,0x3f4e3ec4,
0xbe163f7f,0xbf2c3f62,0xbf043f62,0xbedbbf46,0x3e79bf7b,0x3f71bf0e,0x3f18bf55,0xbd493f7b,0xbeac3f75,0xbf7d3dc9,0xbf2c3f46,0x3f04bf75,
0x3f800000,0x3f780000,0x3f673ec4,0xbf183f6d,0xbf7dbdc9,0xbf3ebef1,0xbf5cbef1,0x3f67bf22,0x3f783e48,0x3eac3f55,0x3f4e3f0e,0xbf803e48,
0xbf71be95,0x3e16bf7f,0xbf3ebf22,0x3f5c3e95,0xbdc93f80,0xbe953f80,0xbf463f35,0xbef1bf35,0x3e95bf7b,0x3f46bf55,0x3f62bf0e,0xbdc93f7b,
0xbef13f6d,0xbf7f3ec4,0xbf753ec4,0x3f22bf6d,0x3f22bf55,0x3f623e48,0x3f7fbe48,0xbf753f0e,0xbf7f0000,0xbf750000,0xbf22bf35,0x3f62bf35,
0x3f753e48,0x3f223f0e,0x3ef13f55,0xbf7f3e48,0xbf62bec4,0xbdc9bf6d,0xbe95bf6d,0x3f463ec4,0x3f463f0e,0xbef13f7b,0x3dc93f7b,0xbe95bf55,
0x3e16bf80,0x3eacbf80,0x3f78bec4,0x3d493f6d,0xbedb3f75,0xbf5c3f46,0xbf803dc9,0x3f18bf75,0x3f2cbf55,0x3f7dbe48,0x3f713e48,0xbf783f0e,
0xbf5c3f22,0xbf2cbef1,0xbf4ebef1,0x3f673dc9,0x3f7d0000,0x3f710000,0x3e793f6d,0xbf803ec4,0xbf67be95,0xbf04bf22,0x3d49bf7f,0x3f4e3e95,
0x3f3e3f0e,0xbe163f7b,0xbeac3f7b,0xbe79bf55,0xbf04bf46,0x3f3ebf62,0x3f18bf62,0xbedb3f7f,0x3f80,0x3e48bf80,0x3f80,0x3f7b0000,
0xbf80,0xbf0e3f6d,0xbf80,0xbf55bec4,0x3f80,0x3f55bf35,0x3f80,0x3f0e3f35,0xbf80,0xbf7b3ec4,0xbf80,0xbe48bf6d,
0xbf800000,0x3f7b0000,0xbf800000,0xbe483f80,0x3f800000,0xbf55bec4,0x3f800000,0x3f0ebf6d,0xbf800000,0x3f0e3f35,0xbf800000,0xbf553f35,
0x3f800000,0xbe48bf6d,0x3f800000,0x3f7bbec4,0x3f3ebf35,0xbf5c3f35,0x3f71bec4,0xbe16bf6d,0xbf4e3f22,0x3f80be95,0xbf783e95,0xbeac3f7f,
0x3f5cbf0e,0xbf67be48,0x3f7dbe48,0x3f3ebf55,0xbf673ef1,0x3f183f22,0xbf803dc9,0xbf783ef1,0x3f2c3f35,0xbf04bf35,0x3eac3f6d,0x3f7dbec4,
0xbf18bf46,0x3d493f75,0xbe79bf75,0xbf71bdc9,0x3f043f55,0x3edbbf7b,0x3e163f7b,0x3f2c3f0e,0xbedbbf62,0xbf4e3f46,0xbd49bf7f,0xbe79bf62,
0xbf7f0000,0x3f750000,0xbf22bf35,0xbf623f35,0x3f753e48,0xbf22bf0e,0x3ef13f55,0x3f7fbe48,0xbf62bec4,0x3dc93f6d,0xbe95bf6d,0xbf46bec4,
0x3f463f0e,0x3ef1bf7b,0x3dc93f7b,0x3e953f55,0x3dc9bf80,0xbe953f80,0x3f46bf35,0xbef1bf35,0xbe953f7b,0x3f46bf55,0xbf623f0e,0xbdc93f7b,
0x3ef1bf6d,0xbf7f3ec4,0x3f75bec4,0x3f22bf6d,0xbf223f55,0x3f623e48,0xbf7f3e48,0xbf753f0e,0x3f183f35,0xbedbbf35,0xbf043f6d,0x3f3e3ec4,
0xbeacbf62,0xbe793f7f,0x3f3ebf46,0xbe16bf62,0x3d493f7b,0x3f4ebf55,0xbf673f0e,0xbf043f7b,0x3e79bf7f,0xbf803e95,0x3f7dbe95,0x3f71bf22,
0xbf4e3f35,0x3f67bf35,0xbf5cbec4,0xbf2c3f6d,0x3f71bef1,0xbf783dc9,0x3f2c3f22,0x3f7dbef1,0xbf803e48,0x3f183f0e,0xbedbbf55,0xbf5cbe48,
0x3f783dc9,0x3d49bf75,0x3e163f75,0x3eac3f46,0x3f80,0xbe483f80,0x3f80,0xbf7b0000,0xbf80,0x3f0ebf6d,0xbf80,0x3f553ec4,
0x3f80,0xbf553f35,0x3f80,0xbf0ebf35,0xbf80,0x3f7bbec4,0xbf80,0x3e483f6d,0xbf800000,0xbf7b0000,0xbf800000,0x3e48bf80,
0x3f800000,0x3f553ec4,0x3f800000,0xbf0e3f6d,0xbf800000,0xbf0ebf35,0xbf800000,0x3f55bf35,0x3f800000,0x3e483f6d,0x3f800000,0xbf7b3ec4,
0x3f800000,0x3f780000,0x3f673ec4,0xbf183f6d,0xbf7dbdc9,0xbf3ebef1,0xbf5cbef1,0x3f67bf22,0x3f783e48,0x3eac3f55,0x3f4e3f0e,0xbf803e48,
0xbf71be95,0x3e16bf7f,0xbf3ebf22,0x3f5c3e95,0xbd493f80,0xbe793f80,0xbedb3f6d,0xbf4ebec4,0x3e16bf7f,0x3f2cbf62,0x3f04bf62,0x3edb3f46,
0xbe793f7b,0xbf713f0e,0xbf183f55,0x3d49bf7b,0x3eacbf75,0x3f7dbdc9,0x3f2cbf46,0xbf043f75,0x3dc9bf80,0x3e95bf80,0x3f46bf35,0x3ef13f35,
0xbe953f7b,0xbf463f55,0xbf623f0e,0x3dc9bf7b,0x3ef1bf6d,0x3f7fbec4,0x3f75bec4,0xbf223f6d,0xbf223f55,0xbf62be48,0xbf7f3e48,0x3f75bf0e,
0x3f7f0000,0x3f750000,0x3f223f35,0xbf623f35,0xbf75be48,0xbf22bf0e,0xbef1bf55,0x3f7fbe48,0x3f623ec4,0x3dc93f6d,0x3e953f6d,0xbf46bec4,
0xbf46bf0e,0x3ef1bf7b,0xbdc9bf7b,0x3e953f55,0xbf7d0000,0xbf710000,0xbe79bf6d,0x3f80bec4,0x3f673e95,0x3f043f22,0xbd493f7f,0xbf4ebe95,
0xbf3ebf0e,0x3e16bf7b,0x3eacbf7b,0x3e793f55,0x3f043f46,0xbf3e3f62,0xbf183f62,0x3edbbf7f,0x3e16bf80,0x3eacbf80,0x3f78bec4,0x3d493f6d,
0xbedb3f75,0xbf5c3f46,0xbf803dc9,0x3f18bf75,0x3f2cbf55,0x3f7dbe48,0x3f713e48,0xbf783f0e,0xbf5c3f22,0xbf2cbef1,0xbf4ebef1,0x3f673dc9,
0x3f80,0x3e48bf80,0x3f80,0x3f7b0000,0xbf80,0xbf0e3f6d,0xbf80,0xbf55bec4,0x3f80,0x3f55bf35,0x3f80,0x3f0e3f35,
0xbf80,0xbf7b3ec4,0xbf80,0xbe48bf6d,0xbf800000,0x3f7b0000,0xbf800000,0xbe483f80,0x3f800000,0xbf55bec4,0x3f800000,0x3f0ebf6d,
0xbf800000,0x3f0e3f35,0xbf800000,0xbf553f35,0x3f800000,0xbe48bf6d,0x3f800000,0x3f7bbec4,0x3f2c3f35,0xbf04bf35,0x3eac3f6d,0x3f7dbec4,
0xbf18bf46,0x3d493f75,0xbe79bf75,0xbf71bdc9,0x3f043f55,0x3edbbf7b,0x3e163f7b,0x3f2c3f0e,0xbedbbf62,0xbf4e3f46,0xbd49bf7f,0xbe79bf62,
0xbf3e3f35,0x3f5cbf35,0xbf713ec4,0x3e163f6d,0x3f4ebf22,0xbf803e95,0x3f78be95,0x3eacbf7f,0xbf5c3f0e,0x3f673e48,0xbf7d3e48,0xbf3e3f55,
0x3f67bef1,0xbf18bf22,0x3f80bdc9,0x3f78bef1,0x3f7f0000,0xbf750000,0x3f223f35,0x3f62bf35,0xbf75be48,0x3f223f0e,0xbef1bf55,0xbf7f3e48,
0x3f623ec4,0xbdc9bf6d,0x3e953f6d,0x3f463ec4,0xbf46bf0e,0xbef13f7b,0xbdc9bf7b,0xbe95bf55,0xbdc93f80,0x3e95bf80,0xbf463f35,0x3ef13f35,
0x3e95bf7b,0xbf463f55,0x3f62bf0e,0x3dc9bf7b,0xbef13f6d,0x3f7fbec4,0xbf753ec4,0xbf223f6d,0x3f22bf55,0xbf62be48,0x3f7fbe48,0x3f75bf0e,
0x3f4ebf35,0xbf673f35,0x3f5c3ec4,0x3f2cbf6d,0xbf713ef1,0x3f78bdc9,0xbf2cbf22,0xbf7d3ef1,0x3f80be48,0xbf18bf0e,0x3edb3f55,0x3f5c3e48,
0xbf78bdc9,0xbd493f75,0xbe16bf75,0xbeacbf46,0x3f183f35,0xbedbbf35,0xbf043f6d,0x3f3e3ec4,0xbeacbf62,0xbe793f7f,0x3f3ebf46,0xbe16bf62,
0x3d493f7b,0x3f4ebf55,0xbf673f0e,0xbf043f7b,0x3e79bf7f,0xbf803e95,0x3f7dbe95,0x3f71bf22,0xbec43f80,0xbf0e3f80,0x3ec4bf80,0x3f550000,
0x3f6dbf35,0x3f7bbec4,0xbf6d3f35,0x3e48bf6d,0xbf6d0000,0xbe48bf35,0x3f6d0000,0xbf7b3f35,0x3ec43f35,0xbf553f6d,0xbec4bf35,0x3f0e3ec4,
0xbf6d0000,0xbf550000,0x3f6d0000,0xbf0e3f80,0x3ec43f35,0xbe483f6d,0xbec4bf35,0x3f7bbec4,0x3ec4bf80,0x3f7bbf35,0xbec43f80,0xbe48bf35,
0xbf6d3f35,0xbf0ebec4,0x3f6dbf35,0xbf553f6d,0xbedb3f80,0xbf183f80,0x3f3ebf6d,0x3f043ec4,0x3f78bf22,0x3f71be95,0xbf7d3e95,0x3f2cbf7f,
0xbf4ebe48,0x3d49bf55,0x3f043f0e,0xbf673e48,0x3d493f62,0xbf783f46,0x3eacbf7f,0xbe163f62,0xbf670000,0xbf4e0000,0x3f2c3ec4,0xbf5c3f6d,
0x3e793f46,0xbeac3f75,0x3e16bf75,0x3f3e3dc9,0x3f18bf7b,0x3f80bf0e,0xbf5c3f55,0x3edbbf7b,0xbf803ef1,0xbe79bf22,0x3f71bdc9,0xbf7d3ef1,
0xbef13f80,0xbf223f80,0x3f75bf35,0x3dc93f35,0x3f7fbf0e,0x3f62be48,0xbf46be48,0x3f75bf55,0xbf22bec4,0x3e95bf6d,0xbdc93f6d,0xbef1bec4,
0xbe953f7b,0xbf7f3f0e,0x3f62bf55,0xbf463f7b,0xbf620000,0xbf460000,0x3e953f35,0xbf7f3f35,0x3dc93f55,0xbef13f7b,0x3f22bf7b,0x3e953f0e,
0x3f46bf6d,0x3f75bec4,0xbf7f3ec4,0x3f62bf6d,0xbf753e48,0x3dc9bf55,0x3ef13f0e,0xbf22be48,0xbf043f80,0xbf2c3f80,0x3f7dbec4,0xbeac3f6d,
0x3f80bef1,0x3f4ebdc9,0xbeacbf22,0x3f78bef1,0xbedbbf0e,0x3f04bf7b,0xbf2c3f7b,0x3e16bf55,0xbf183f7f,0xbf673e95,0x3f78be95,0xbf803f22,
0xbf5c0000,0xbf3e0000,0xbe163f6d,0xbf713ec4,0xbd493f62,0xbf183f7f,0x3f71bf46,0xbe793f62,0x3f67bf55,0x3f5cbe48,0xbf3ebe48,0x3f7dbf0e,
0xbf4ebdc9,0x3edbbf75,0xbe793f75,0x3d49bf46,0xbec43f80,0x3f0ebf80,0x3ec4bf80,0xbf550000,0x3f6dbf35,0xbf7b3ec4,0xbf6d3f35,0xbe483f6d,
0xbf6d0000,0x3e483f35,0x3f6d0000,0x3f7bbf35,0x3ec43f35,0x3f55bf6d,0xbec4bf35,0xbf0ebec4,0xbf6d0000,0x3f550000,0x3f6d0000,0x3f0ebf80,
0x3ec43f35,0x3e48bf6d,0xbec4bf35,0xbf7b3ec4,0x3ec4bf80,0xbf7b3f35,0xbec43f80,0x3e483f35,0xbf6d3f35,0x3f0e3ec4,0x3f6dbf35,0x3f55bf6d,
0xbf713f35,0x3f7dbf35,0x3f80bec4,0x3e79bf6d,0x3f5c3dc9,0xbedbbef1,0xbf18bef1,0xbf803f22,0xbe16bf55,0xbf3e3f7b,0xbe793f7b,0x3eac3f0e,
0xbf2c3f75,0x3f5cbdc9,0x3f67bf46,0x3f4ebf75,0xbeacbf35,0x3e163f35,0xbd493f6d,0x3f78bec4,0xbf043f7f,0x3f67bf62,0x3f4ebf62,0xbd49bf46,
0x3f7dbf0e,0xbf2cbe48,0xbf783e48,0xbf713f55,0xbf3ebe95,0xbf043f7f,0x3edb3f22,0x3f183e95,0xbf620000,0x3f460000,0x3e953f35,0x3f7fbf35,
0x3dc93f55,0x3ef1bf7b,0x3f22bf7b,0xbe95bf0e,0x3f46bf6d,0xbf753ec4,0xbf7f3ec4,0xbf623f6d,0xbf753e48,0xbdc93f55,0x3ef13f0e,0x3f223e48,
0x3ef1bf80,0xbf223f80,0xbf753f35,0x3dc93f35,0xbf7f3f0e,0x3f62be48,0x3f463e48,0x3f75bf55,0x3f223ec4,0x3e95bf6d,0x3dc9bf6d,0xbef1bec4,
0x3e95bf7b,0xbf7f3f0e,0xbf623f55,0xbf463f7b,0xbe79bf35,0x3d493f35,0xbf4e3f6d,0x3edb3ec4,0xbf3e3f75,0x3f7dbf46,0x3f67bdc9,0x3f5cbf75,
0x3f71be48,0xbe79bf0e,0xbd49bf55,0xbf18be48,0xbe16bf46,0xbf713f62,0xbf5c3f62,0xbf3e3f7f,0x3f78bf35,0xbf803f35,0xbf18bec4,0xbf673f6d,
0xbf2cbe95,0x3e163f22,0xbedb3f7f,0x3f043e95,0xbeac3f7b,0x3f78bf55,0x3f80bf0e,0x3f4ebf7b,0x3f7dbf22,0xbeacbef1,0xbf04bef1,0xbf2cbdc9,
0xbec43f80,0xbf0e3f80,0x3ec4bf80,0x3f550000,0x3f6dbf35,0x3f7bbec4,0xbf6d3f35,0x3e48bf6d,0xbf6d0000,0xbe48bf35,0x3f6d0000,0xbf7b3f35,
0x3ec43f35,0xbf553f6d,0xbec4bf35,0x3f0e3ec4,0xbf6d0000,0xbf550000,0x3f6d0000,0xbf0e3f80,0x3ec43f35,0xbe483f6d,0xbec4bf35,0x3f7bbec4,
0x3ec4bf80,0x3f7bbf35,0xbec43f80,0xbe48bf35,0xbf6d3f35,0xbf0ebec4,0x3f6dbf35,0xbf553f6d,0xbf670000,0xbf4e0000,0x3f2c3ec4,0xbf5c3f6d,
0x3e793f46,0xbeac3f75,0x3e16bf75,0x3f3e3dc9,0x3f18bf7b,0x3f80bf0e,0xbf5c3f55,0x3edbbf7b,0xbf803ef1,0xbe79bf22,0x3f71bdc9,0xbf7d3ef1,
0x3edbbf80,0x3f18bf80,0xbf3e3f6d,0xbf04bec4,0xbf783f22,0xbf713e95,0x3f7dbe95,0xbf2c3f7f,0x3f4e3e48,0xbd493f55,0xbf04bf0e,0x3f67be48,
0xbd49bf62,0x3f78bf46,0xbeac3f7f,0x3e16bf62,0x3ef1bf80,0x3f22bf80,0xbf753f35,0xbdc9bf35,0xbf7f3f0e,0xbf623e48,0x3f463e48,0xbf753f55,
0x3f223ec4,0xbe953f6d,0x3dc9bf6d,0x3ef13ec4,0x3e95bf7b,0x3f7fbf0e,0xbf623f55,0x3f46bf7b,0x3f620000,0x3f460000,0xbe95bf35,0x3f7fbf35,
0xbdc9bf55,0x3ef1bf7b,0xbf223f7b,0xbe95bf0e,0xbf463f6d,0xbf753ec4,0x3f7fbec4,0xbf623f6d,0x3f75be48,0xbdc93f55,0xbef1bf0e,0x3f223e48,
0x3f5c0000,0x3f3e0000,0x3e16bf6d,0x3f71bec4,0x3d49bf62,0x3f18bf7f,0xbf713f46,0x3e79bf62,0xbf673f55,0xbf5c3e48,0x3f3e3e48,0xbf7d3f0e,
0x3f4e3dc9,0xbedb3f75,0x3e79bf75,0xbd493f46,0xbf043f80,0xbf2c3f80,0x3f7dbec4,0xbeac3f6d,0x3f80bef1,0x3f4ebdc9,0xbeacbf22,0x3f78bef1,
0xbedbbf0e,0x3f04bf7b,0xbf2c3f7b,0x3e16bf55,0xbf183f7f,0xbf673e95,0x3f78be95,0xbf803f22,0xbec43f80,0x3f0ebf80,0x3ec4bf80,0xbf550000,
0x3f6dbf35,0xbf7b3ec4,0xbf6d3f35,0xbe483f6d,0xbf6d0000,0x3e483f35,0x3f6d0000,0x3f7bbf35,0x3ec43f35,0x3f55bf6d,0xbec4bf35,0xbf0ebec4,
0xbf6d0000,0x3f550000,0x3f6d0000,0x3f0ebf80,0x3ec43f35,0x3e48bf6d,0xbec4bf35,0xbf7b3ec4,0x3ec4bf80,0xbf7b3f35,0xbec43f80,0x3e483f35,
0xbf6d3f35,0x3f0e3ec4,0x3f6dbf35,0x3f55bf6d,0xbeacbf35,0x3e163f35,0xbd493f6d,0x3f78bec4,0xbf043f7f,0x3f67bf62,0x3f4ebf62,0xbd49bf46,
0x3f7dbf0e,0xbf2cbe48,0xbf783e48,0xbf713f55,0xbf3ebe95,0xbf043f7f,0x3edb3f22,0x3f183e95,0x3f71bf35,0xbf7d3f35,0xbf803ec4,0xbe793f6d,
0xbf5cbdc9,0x3edb3ef1,0x3f183ef1,0x3f80bf22,0x3e163f55,0x3f3ebf7b,0x3e79bf7b,0xbeacbf0e,0x3f2cbf75,0xbf5c3dc9,0xbf673f46,0xbf4e3f75,
0x3f620000,0xbf460000,0xbe95bf35,0xbf7f3f35,0xbdc9bf55,0xbef13f7b,0xbf223f7b,0x3e953f0e,0xbf463f6d,0x3f75bec4,0x3f7fbec4,0x3f62bf6d,
0x3f75be48,0x3dc9bf55,0xbef1bf0e,0xbf22be48,0xbef13f80,0x3f22bf80,0x3f75bf35,0xbdc9bf35,0x3f7fbf0e,0xbf623e48,0xbf46be48,0xbf753f55,
0xbf22bec4,0xbe953f6d,0xbdc93f6d,0x3ef13ec4,0xbe953f7b,0x3f7fbf0e,0x3f62bf55,0x3f46bf7b,0xbf783f35,0x3f80bf35,0x3f183ec4,0x3f67bf6d,
0x3f2c3e95,0xbe16bf22,0x3edbbf7f,0xbf04be95,0x3eacbf7b,0xbf783f55,0xbf803f0e,0xbf4e3f7b,0xbf7d3f22,0x3eac3ef1,0x3f043ef1,0x3f2c3dc9,
0xbe79bf35,0x3d493f35,0xbf4e3f6d,0x3edb3ec4,0xbf3e3f75,0x3f7dbf46,0x3f67bdc9,0x3f5cbf75,0x3f71be48,0xbe79bf0e,0xbd49bf55,0xbf18be48,
0xbe16bf46,0xbf713f62,0xbf5c3f62,0xbf3e3f7f,0xbec43f80,0xbf0e3f80,0x3ec4bf80,0x3f550000,0x3f6dbf35,0x3f7bbec4,0xbf6d3f35,0x3e48bf6d,
0xbf6d0000,0xbe48bf35,0x3f6d0000,0xbf7b3f35,0x3ec43f35,0xbf553f6d,0xbec4bf35,0x3f0e3ec4,0xbf6d0000,0xbf550000,0x3f6d0000,0xbf0e3f80,
0x3ec43f35,0xbe483f6d,0xbec4bf35,0x3f7bbec4,0x3ec4bf80,0x3f7bbf35,0xbec43f80,0xbe48bf35,0xbf6d3f35,0xbf0ebec4,0x3f6dbf35,0xbf553f6d,
0x3edbbf80,0x3f18bf80,0xbf3e3f6d,0xbf04bec4,0xbf783f22,0xbf713e95,0x3f7dbe95,0xbf2c3f7f,0x3f4e3e48,0xbd493f55,0xbf04bf0e,0x3f67be48,
0xbd49bf62,0x3f78bf46,0xbeac3f7f,0x3e16bf62,0x3f670000,0x3f4e0000,0xbf2cbec4,0x3f5cbf6d,0xbe79bf46,0x3eacbf75,0xbe163f75,0xbf3ebdc9,
0xbf183f7b,0xbf803f0e,0x3f5cbf55,0xbedb3f7b,0x3f80bef1,0x3e793f22,0xbf713dc9,0x3f7dbef1,0xbef13f80,0xbf223f80,0x3f75bf35,0x3dc93f35,
0x3f7fbf0e,0x3f62be48,0xbf46be48,0x3f75bf55,0xbf22bec4,0x3e95bf6d,0xbdc93f6d,0xbef1bec4,0xbe953f7b,0xbf7f3f0e,0x3f62bf55,0xbf463f7b,
0xbf620000,0xbf460000,0x3e953f35,0xbf7f3f35,0x3dc93f55,0xbef13f7b,0x3f22bf7b,0x3e953f0e,0x3f46bf6d,0x3f75bec4,0xbf7f3ec4,0x3f62bf6d,
0xbf753e48,0x3dc9bf55,0x3ef13f0e,0xbf22be48,0x3f04bf80,0x3f2cbf80,0xbf7d3ec4,0x3eacbf6d,0xbf803ef1,0xbf4e3dc9,0x3eac3f22,0xbf783ef1,
0x3edb3f0e,0xbf043f7b,0x3f2cbf7b,0xbe163f55,0x3f18bf7f,0x3f67be95,0xbf783e95,0x3f80bf22,0x3f5c0000,0x3f3e0000,0x3e16bf6d,0x3f71bec4,
0x3d49bf62,0x3f18bf7f,0xbf713f46,0x3e79bf62,0xbf673f55,0xbf5c3e48,0x3f3e3e48,0xbf7d3f0e,0x3f4e3dc9,0xbedb3f75,0x3e79bf75,0xbd493f46,
0xbec43f80,0x3f0ebf80,0x3ec4bf80,0xbf550000,0x3f6dbf35,0xbf7b3ec4,0xbf6d3f35,0xbe483f6d,0xbf6d0000,0x3e483f35,0x3f6d0000,0x3f7bbf35,
0x3ec43f35,0x3f55bf6d,0xbec4bf35,0xbf0ebec4,0xbf6d0000,0x3f550000,0x3f6d0000,0x3f0ebf80,0x3ec43f35,0x3e48bf6d,0xbec4bf35,0xbf7b3ec4,
0x3ec4bf80,0xbf7b3f35,0xbec43f80,0x3e483f35,0xbf6d3f35,0x3f0e3ec4,0x3f6dbf35,0x3f55bf6d,0x3f71bf35,0xbf7d3f35,0xbf803ec4,0xbe793f6d,
0xbf5cbdc9,0x3edb3ef1,0x3f183ef1,0x3f80bf22,0x3e163f55,0x3f3ebf7b,0x3e79bf7b,0xbeacbf0e,0x3f2cbf75,0xbf5c3dc9,0xbf673f46,0xbf4e3f75,
0x3eac3f35,0xbe16bf35,0x3d49bf6d,0xbf783ec4,0x3f04bf7f,0xbf673f62,0xbf4e3f62,0x3d493f46,0xbf7d3f0e,0x3f2c3e48,0x3f78be48,0x3f71bf55,
0x3f3e3e95,0x3f04bf7f,0xbedbbf22,0xbf18be95,0xbf620000,0x3f460000,0x3e953f35,0x3f7fbf35,0x3dc93f55,0x3ef1bf7b,0x3f22bf7b,0xbe95bf0e,
0x3f46bf6d,0xbf753ec4,0xbf7f3ec4,0xbf623f6d,0xbf753e48,0xbdc93f55,0x3ef13f0e,0x3f223e48,0x3ef1bf80,0xbf223f80,0xbf753f35,0x3dc93f35,
0xbf7f3f0e,0x3f62be48,0x3f463e48,0x3f75bf55,0x3f223ec4,0x3e95bf6d,0x3dc9bf6d,0xbef1bec4,0x3e95bf7b,0xbf7f3f0e,0xbf623f55,0xbf463f7b,
0x3e793f35,0xbd49bf35,0x3f4ebf6d,0xbedbbec4,0x3f3ebf75,0xbf7d3f46,0xbf673dc9,0xbf5c3f75,0xbf713e48,0x3e793f0e,0x3d493f55,0x3f183e48,
0x3e163f46,0x3f71bf62,0x3f5cbf62,0x3f3ebf7f,0xbf783f35,0x3f80bf35,0x3f183ec4,0x3f67bf6d,0x3f2c3e95,0xbe16bf22,0x3edbbf7f,0xbf04be95,
0x3eacbf7b,0xbf783f55,0xbf803f0e,0xbf4e3f7b,0xbf7d3f22,0x3eac3ef1,0x3f043ef1,0x3f2c3dc9,0xbec43f80,0xbf0e3f80,0x3ec4bf80,0x3f550000,
0x3f6dbf35,0x3f7bbec4,0xbf6d3f35,0x3e48bf6d,0xbf6d0000,0xbe48bf35,0x3f6d0000,0xbf7b3f35,0x3ec43f35,0xbf553f6d,0xbec4bf35,0x3f0e3ec4,
0xbf6d0000,0xbf550000,0x3f6d0000,0xbf0e3f80,0x3ec43f35,0xbe483f6d,0xbec4bf35,0x3f7bbec4,0x3ec4bf80,0x3f7bbf35,0xbec43f80,0xbe48bf35,
0xbf6d3f35,0xbf0ebec4,0x3f6dbf35,0xbf553f6d,0x3f670000,0x3f4e0000,0xbf2cbec4,0x3f5cbf6d,0xbe79bf46,0x3eacbf75,0xbe163f75,0xbf3ebdc9,
0xbf183f7b,0xbf803f0e,0x3f5cbf55,0xbedb3f7b,0x3f80bef1,0x3e793f22,0xbf713dc9,0x3f7dbef1,0xbedb3f80,0xbf183f80,0x3f3ebf6d,0x3f043ec4,
0x3f78bf22,0x3f71be95,0xbf7d3e95,0x3f2cbf7f,0xbf4ebe48,0x3d49bf55,0x3f043f0e,0xbf673e48,0x3d493f62,0xbf783f46,0x3eacbf7f,0xbe163f62,
0x3ef1bf80,0x3f22bf80,0xbf753f35,0xbdc9bf35,0xbf7f3f0e,0xbf623e48,0x3f463e48,0xbf753f55,0x3f223ec4,0xbe953f6d,0x3dc9bf6d,0x3ef13ec4,
0x3e95bf7b,0x3f7fbf0e,0xbf623f55,0x3f46bf7b,0x3f620000,0x3f460000,0xbe95bf35,0x3f7fbf35,0xbdc9bf55,0x3ef1bf7b,0xbf223f7b,0xbe95bf0e,
0xbf463f6d,0xbf753ec4,0x3f7fbec4,0xbf623f6d,0x3f75be48,0xbdc93f55,0xbef1bf0e,0x3f223e48,0xbf5c0000,0xbf3e0000,0xbe163f6d,0xbf713ec4,
0xbd493f62,0xbf183f7f,0x3f71bf46,0xbe793f62,0x3f67bf55,0x3f5cbe48,0xbf3ebe48,0x3f7dbf0e,0xbf4ebdc9,0x3edbbf75,0xbe793f75,0x3d49bf46,
0x3f04bf80,0x3f2cbf80,0xbf7d3ec4,0x3eacbf6d,0xbf803ef1,0xbf4e3dc9,0x3eac3f22,0xbf783ef1,0x3edb3f0e,0xbf043f7b,0x3f2cbf7b,0xbe163f55,
0x3f18bf7f,0x3f67be95,0xbf783e95,0x3f80bf22,0xbec43f80,0x3f0ebf80,0x3ec4bf80,0xbf550000,0x3f6dbf35,0xbf7b3ec4,0xbf6d3f35,0xbe483f6d,
0xbf6d0000,0x3e483f35,0x3f6d0000,0x3f7bbf35,0x3ec43f35,0x3f55bf6d,0xbec4bf35,0xbf0ebec4,0xbf6d0000,0x3f550000,0x3f6d0000,0x3f0ebf80,
0x3ec43f35,0x3e48bf6d,0xbec4bf35,0xbf7b3ec4,0x3ec4bf80,0xbf7b3f35,0xbec43f80,0x3e483f35,0xbf6d3f35,0x3f0e3ec4,0x3f6dbf35,0x3f55bf6d,
0x3eac3f35,0xbe16bf35,0x3d49bf6d,0xbf783ec4,0x3f04bf7f,0xbf673f62,0xbf4e3f62,0x3d493f46,0xbf7d3f0e,0x3f2c3e48,0x3f78be48,0x3f71bf55,
0x3f3e3e95,0x3f04bf7f,0xbedbbf22,0xbf18be95,0xbf713f35,0x3f7dbf35,0x3f80bec4,0x3e79bf6d,0x3f5c3dc9,0xbedbbef1,0xbf18bef1,0xbf803f22,
0xbe16bf55,0xbf3e3f7b,0xbe793f7b,0x3eac3f0e,0xbf2c3f75,0x3f5cbdc9,0x3f67bf46,0x3f4ebf75,0x3f620000,0xbf460000,0xbe95bf35,0xbf7f3f35,
0xbdc9bf55,0xbef13f7b,0xbf223f7b,0x3e953f0e,0xbf463f6d,0x3f75bec4,0x3f7fbec4,0x3f62bf6d,0x3f75be48,0x3dc9bf55,0xbef1bf0e,0xbf22be48,
0xbef13f80,0x3f22bf80,0x3f75bf35,0xbdc9bf35,0x3f7fbf0e,0xbf623e48,0xbf46be48,0xbf753f55,0xbf22bec4,0xbe953f6d,0xbdc93f6d,0x3ef13ec4,
0xbe953f7b,0x3f7fbf0e,0x3f62bf55,0x3f46bf7b,0x3f78bf35,0xbf803f35,0xbf18bec4,0xbf673f6d,0xbf2cbe95,0x3e163f22,0xbedb3f7f,0x3f043e95,
0xbeac3f7b,0x3f78bf55,0x3f80bf0e,0x3f4ebf7b,0x3f7dbf22,0xbeacbef1,0xbf04bef1,0xbf2cbdc9,0x3e793f35,0xbd49bf35,0x3f4ebf6d,0xbedbbec4,
0x3f3ebf75,0xbf7d3f46,0xbf673dc9,0xbf5c3f75,0xbf713e48,0x3e793f0e,0x3d493f55,0x3f183e48,0x3e163f46,0x3f71bf62,0x3f5cbf62,0x3f3ebf7f,
0xbf353f80,0xbf553f80,0xbf353f80,0xbf0e0000,0x3f350000,0x3e483ec4,0x3f350000,0xbf7b3f6d,0x3f35bf80,0x3f7bbf35,0x3f35bf80,0xbe483f35,
0xbf350000,0x3f0ebf6d,0xbf350000,0x3f55bec4,0xbf350000,0xbf0e0000,0xbf350000,0x3f55bf80,0xbf353f80,0xbf7b3f6d,0xbf353f80,0xbe48bec4,
0x3f350000,0xbe483f35,0x3f350000,0xbf7b3f35,0x3f35bf80,0x3f55bec4,0x3f35bf80,0xbf0e3f6d,0xbf3e3f80,0xbf5c3f80,0xbf713f6d,0xbe16bec4,
0x3f183dc9,0x3d493ef1,0x3e793ef1,0xbf713f22,0x3f5cbf7b,0x3f67bf0e,0x3f7dbf55,0xbf3e3f7b,0xbedbbe95,0x3f4ebf7f,0xbd49bf22,0x3e793e95,
0xbf2c0000,0xbf040000,0xbeacbec4,0x3f7dbf6d,0xbf4e3f7f,0xbf803f62,0xbf783f62,0x3eacbf46,0x3f043e48,0xbedb3f55,0x3e163f0e,0xbf2c3e48,
0x3f67bf75,0x3f18bdc9,0x3f80bf46,0xbf783f75,0xbf463f80,0xbf623f80,0xbf7f3f35,0x3e95bf35,0x3ef13e48,0xbdc93f0e,0xbe953f55,0xbf223e48,
0x3f75bf6d,0x3f46bec4,0x3f62bec4,0xbf7f3f6d,0xbdc9bf0e,0x3f75bf7b,0x3f22bf7b,0xbef13f55,0xbf220000,0xbef10000,0x3dc9bf35,0x3f75bf35,
0xbf623f7b,0xbf7f3f55,0xbf753f0e,0x3f46bf7b,0x3e953ec4,0xbf223f6d,0xbef13f6d,0xbdc9bec4,0x3f7fbf55,0x3e953e48,0x3f46be48,0xbf623f0e,
0xbf4e3f80,0xbf673f80,0xbf5c3ec4,0x3f2cbf6d,0x3eac3e95,0xbe793f22,0xbf3e3f7f,0xbe16be95,0x3f80bf55,0x3f18be48,0x3edb3e48,0xbf5c3f0e,
0x3e79bf46,0x3f80bf62,0x3f7dbf62,0xbf713f7f,0xbf180000,0xbedb0000,0x3f04bf6d,0x3f3ebec4,0xbf713f75,0xbf783f46,0xbf2c3dc9,0x3f7dbf75,
0x3d493f0e,0xbf4e3f7b,0xbf673f7b,0x3f04bf55,0x3f78bf22,0xbd493ef1,0x3e163ef1,0xbeacbdc9,0xbf353f80,0x3f55bf80,0xbf353f80,0x3f0e0000,
0x3f350000,0xbe48bec4,0x3f350000,0x3f7bbf6d,0x3f35bf80,0xbf7b3f35,0x3f35bf80,0x3e48bf35,0xbf350000,0xbf0e3f6d,0xbf350000,0xbf553ec4,
0xbf350000,0x3f0e0000,0xbf350000,0xbf553f80,0xbf353f80,0x3f7bbf6d,0xbf353f80,0x3e483ec4,0x3f350000,0x3e48bf35,0x3f350000,0x3f7bbf35,
0x3f35bf80,0xbf553ec4,0x3f35bf80,0x3f0ebf6d,0xbf803f35,0x3f78bf35,0xbf673ec4,0xbf183f6d,0xbe163f46,0x3f2cbf75,0xbf043f75,0x3edb3dc9,
0x3f78bf0e,0xbeacbe48,0x3f4ebe48,0x3f80bf55,0x3eacbf62,0xbf7d3f46,0x3f2cbf7f,0x3f04bf62,0x3d49bf35,0xbe793f35,0x3edbbf6d,0xbf4e3ec4,
0xbf7d3f22,0x3f3ebe95,0xbf5c3e95,0xbf673f7f,0xbe793f55,0x3f71bf7b,0xbf183f7b,0xbd493f0e,0x3f71bef1,0x3e16bf22,0x3f3ebdc9,0x3f5cbef1,
0xbf220000,0x3ef10000,0x3dc9bf35,0xbf753f35,0xbf623f7b,0x3f7fbf55,0xbf753f0e,0xbf463f7b,0x3e953ec4,0x3f22bf6d,0xbef13f6d,0x3dc93ec4,
0x3f7fbf55,0xbe95be48,0x3f46be48,0x3f62bf0e,0x3f46bf80,0xbf623f80,0x3f7fbf35,0x3e95bf35,0xbef1be48,0xbdc93f0e,0x3e95bf55,0xbf223e48,
0xbf753f6d,0x3f46bec4,0xbf623ec4,0xbf7f3f6d,0x3dc93f0e,0x3f75bf7b,0xbf223f7b,0xbef13f55,0x3e16bf35,0xbeac3f35,0x3f78bf6d,0xbd49bec4,
0xbf673ef1,0x3f04bdc9,0x3d49bf22,0xbf4e3ef1,0xbf2c3f7b,0x3f7dbf55,0xbf713f0e,0xbf783f7b,0x3f043dc9,0x3f3ebf75,0xbf183f75,0xbedb3f46,
0x3f7dbf35,0xbf713f35,0x3e793ec4,0x3f80bf6d,0x3edbbf62,0xbf5c3f7f,0x3f80bf46,0x3f18bf62,0xbf3e3e48,0xbe163f0e,0x3eacbf55,0xbe79be48,
0xbf5c3f7f,0x3f2cbe95,0xbf4e3e95,0xbf673f22,0xbf353f80,0xbf553f80,0xbf353f80,0xbf0e0000,0x3f350000,0x3e483ec4,0x3f350000,0xbf7b3f6d,
0x3f35bf80,0x3f7bbf35,0x3f35bf80,0xbe483f35,0xbf350000,0x3f0ebf6d,0xbf350000,0x3f55bec4,0xbf350000,0xbf0e0000,0xbf350000,0x3f55bf80,
0xbf353f80,0xbf7b3f6d,0xbf353f80,0xbe48bec4,0x3f350000,0xbe483f35,0x3f350000,0xbf7b3f35,0x3f35bf80,0x3f55bec4,0x3f35bf80,0xbf0e3f6d,
0xbf2c0000,0xbf040000,0xbeacbec4,0x3f7dbf6d,0xbf4e3f7f,0xbf803f62,0xbf783f62,0x3eacbf46,0x3f043e48,0xbedb3f55,0x3e163f0e,0xbf2c3e48,
0x3f67bf75,0x3f18bdc9,0x3f80bf46,0xbf783f75,0x3f3ebf80,0x3f5cbf80,0x3f71bf6d,0x3e163ec4,0xbf18bdc9,0xbd49bef1,0xbe79bef1,0x3f71bf22,
0xbf5c3f7b,0xbf673f0e,0xbf7d3f55,0x3f3ebf7b,0x3edb3e95,0xbf4e3f7f,0x3d493f22,0xbe79be95,0x3f46bf80,0x3f62bf80,0x3f7fbf35,0xbe953f35,
0xbef1be48,0x3dc9bf0e,0x3e95bf55,0x3f22be48,0xbf753f6d,0xbf463ec4,0xbf623ec4,0x3f7fbf6d,0x3dc93f0e,0xbf753f7b,0xbf223f7b,0x3ef1bf55,
0x3f220000,0x3ef10000,0xbdc93f35,0xbf753f35,0x3f62bf7b,0x3f7fbf55,0x3f75bf0e,0xbf463f7b,0xbe95bec4,0x3f22bf6d,0x3ef1bf6d,0x3dc93ec4,
0xbf7f3f55,0xbe95be48,0xbf463e48,0x3f62bf0e,0x3f180000,0x3edb0000,0xbf043f6d,0xbf3e3ec4,0x3f71bf75,0x3f78bf46,0x3f2cbdc9,0xbf7d3f75,
0xbd49bf0e,0x3f4ebf7b,0x3f67bf7b,0xbf043f55,0xbf783f22,0x3d49bef1,0xbe16bef1,0x3eac3dc9,0xbf4e3f80,0xbf673f80,0xbf5c3ec4,0x3f2cbf6d,
0x3eac3e95,0xbe793f22,0xbf3e3f7f,0xbe16be95,0x3f80bf55,0x3f18be48,0x3edb3e48,0xbf5c3f0e,0x3e79bf46,0x3f80bf62,0x3f7dbf62,0xbf713f7f,
0xbf353f80,0x3f55bf80,0xbf353f80,0x3f0e0000,0x3f350000,0xbe48bec4,0x3f350000,0x3f7bbf6d,0x3f35bf80,0xbf7b3f35,0x3f35bf80,0x3e48bf35,
0xbf350000,0xbf0e3f6d,0xbf350000,0xbf553ec4,0xbf350000,0x3f0e0000,0xbf350000,0xbf553f80,0xbf353f80,0x3f7bbf6d,0xbf353f80,0x3e483ec4,
0x3f350000,0x3e48bf35,0x3f350000,0x3f7bbf35,0x3f35bf80,0xbf553ec4,0x3f35bf80,0x3f0ebf6d,0x3d49bf35,0xbe793f35,0x3edbbf6d,0xbf4e3ec4,
0xbf7d3f22,0x3f3ebe95,0xbf5c3e95,0xbf673f7f,0xbe793f55,0x3f71bf7b,0xbf183f7b,0xbd493f0e,0x3f71bef1,0x3e16bf22,0x3f3ebdc9,0x3f5cbef1,
0x3f80bf35,0xbf783f35,0x3f67bec4,0x3f18bf6d,0x3e16bf46,0xbf2c3f75,0x3f04bf75,0xbedbbdc9,0xbf783f0e,0x3eac3e48,0xbf4e3e48,0xbf803f55,
0xbeac3f62,0x3f7dbf46,0xbf2c3f7f,0xbf043f62,0x3f220000,0xbef10000,0xbdc93f35,0x3f75bf35,0x3f62bf7b,0xbf7f3f55,0x3f75bf0e,0x3f46bf7b,
0xbe95bec4,0xbf223f6d,0x3ef1bf6d,0xbdc9bec4,0xbf7f3f55,0x3e953e48,0xbf463e48,0xbf623f0e,0xbf463f80,0x3f62bf80,0xbf7f3f35,0xbe953f35,
0x3ef13e48,0x3dc9bf0e,0xbe953f55,0x3f22be48,0x3f75bf6d,0xbf463ec4,0x3f62bec4,0x3f7fbf6d,0xbdc9bf0e,0xbf753f7b,0x3f22bf7b,0x3ef1bf55,
0xbf7d3f35,0x3f71bf35,0xbe79bec4,0xbf803f6d,0xbedb3f62,0x3f5cbf7f,0xbf803f46,0xbf183f62,0x3f3ebe48,0x3e16bf0e,0xbeac3f55,0x3e793e48,
0x3f5cbf7f,0xbf2c3e95,0x3f4ebe95,0x3f67bf22,0x3e16bf35,0xbeac3f35,0x3f78bf6d,0xbd49bec4,0xbf673ef1,0x3f04bdc9,0x3d49bf22,0xbf4e3ef1,
0xbf2c3f7b,0x3f7dbf55,0xbf713f0e,0xbf783f7b,0x3f043dc9,0x3f3ebf75,0xbf183f75,0xbedb3f46,0xbf353f80,0xbf553f80,0xbf353f80,0xbf0e0000,
0x3f350000,0x3e483ec4,0x3f350000,0xbf7b3f6d,0x3f35bf80,0x3f7bbf35,0x3f35bf80,0xbe483f35,0xbf350000,0x3f0ebf6d,0xbf350000,0x3f55bec4,
0xbf350000,0xbf0e0000,0xbf350000,0x3f55bf80,0xbf353f80,0xbf7b3f6d,0xbf353f80,0xbe48bec4,0x3f350000,0xbe483f35,0x3f350000,0xbf7b3f35,
0x3f35bf80,0x3f55bec4,0x3f35bf80,0xbf0e3f6d,0x3f3ebf80,0x3f5cbf80,0x3f71bf6d,0x3e163ec4,0xbf18bdc9,0xbd49bef1,0xbe79bef1,0x3f71bf22,
0xbf5c3f7b,0xbf673f0e,0xbf7d3f55,0x3f3ebf7b,0x3edb3e95,0xbf4e3f7f,0x3d493f22,0xbe79be95,0x3f2c0000,0x3f040000,0x3eac3ec4,0xbf7d3f6d,
0x3f4ebf7f,0x3f80bf62,0x3f78bf62,0xbeac3f46,0xbf04be48,0x3edbbf55,0xbe16bf0e,0x3f2cbe48,0xbf673f75,0xbf183dc9,0xbf803f46,0x3f78bf75,
0xbf463f80,0xbf623f80,0xbf7f3f35,0x3e95bf35,0x3ef13e48,0xbdc93f0e,0xbe953f55,0xbf223e48,0x3f75bf6d,0x3f46bec4,0x3f62bec4,0xbf7f3f6d,
0xbdc9bf0e,0x3f75bf7b,0x3f22bf7b,0xbef13f55,0xbf220000,0xbef10000,0x3dc9bf35,0x3f75bf35,0xbf623f7b,0xbf7f3f55,0xbf753f0e,0x3f46bf7b,
0x3e953ec4,0xbf223f6d,0xbef13f6d,0xbdc9bec4,0x3f7fbf55,0x3e953e48,0x3f46be48,0xbf623f0e,0x3f4ebf80,0x3f67bf80,0x3f5cbec4,0xbf2c3f6d,
0xbeacbe95,0x3e79bf22,0x3f3ebf7f,0x3e163e95,0xbf803f55,0xbf183e48,0xbedbbe48,0x3f5cbf0e,0xbe793f46,0xbf803f62,0xbf7d3f62,0x3f71bf7f,
0x3f180000,0x3edb0000,0xbf043f6d,0xbf3e3ec4,0x3f71bf75,0x3f78bf46,0x3f2cbdc9,0xbf7d3f75,0xbd49bf0e,0x3f4ebf7b,0x3f67bf7b,0xbf043f55,
0xbf783f22,0x3d49bef1,0xbe16bef1,0x3eac3dc9,0xbf353f80,0x3f55bf80,0xbf353f80,0x3f0e0000,0x3f350000,0xbe48bec4,0x3f350000,0x3f7bbf6d,
0x3f35bf80,0xbf7b3f35,0x3f35bf80,0x3e48bf35,0xbf350000,0xbf0e3f6d,0xbf350000,0xbf553ec4,0xbf350000,0x3f0e0000,0xbf350000,0xbf553f80,
0xbf353f80,0x3f7bbf6d,0xbf353f80,0x3e483ec4,0x3f350000,0x3e48bf35,0x3f350000,0x3f7bbf35,0x3f35bf80,0xbf553ec4,0x3f35bf80,0x3f0ebf6d,
0x3f80bf35,0xbf783f35,0x3f67bec4,0x3f18bf6d,0x3e16bf46,0xbf2c3f75,0x3f04bf75,0xbedbbdc9,0xbf783f0e,0x3eac3e48,0xbf4e3e48,0xbf803f55,
0xbeac3f62,0x3f7dbf46,0xbf2c3f7f,0xbf043f62,0xbd493f35,0x3e79bf35,0xbedb3f6d,0x3f4ebec4,0x3f7dbf22,0xbf3e3e95,0x3f5cbe95,0x3f67bf7f,
0x3e79bf55,0xbf713f7b,0x3f18bf7b,0x3d49bf0e,0xbf713ef1,0xbe163f22,0xbf3e3dc9,0xbf5c3ef1,0xbf220000,0x3ef10000,0x3dc9bf35,0xbf753f35,
0xbf623f7b,0x3f7fbf55,0xbf753f0e,0xbf463f7b,0x3e953ec4,0x3f22bf6d,0xbef13f6d,0x3dc93ec4,0x3f7fbf55,0xbe95be48,0x3f46be48,0x3f62bf0e,
0x3f46bf80,0xbf623f80,0x3f7fbf35,0x3e95bf35,0xbef1be48,0xbdc93f0e,0x3e95bf55,0xbf223e48,0xbf753f6d,0x3f46bec4,0xbf623ec4,0xbf7f3f6d,
0x3dc93f0e,0x3f75bf7b,0xbf223f7b,0xbef13f55,0xbe163f35,0x3eacbf35,0xbf783f6d,0x3d493ec4,0x3f67bef1,0xbf043dc9,0xbd493f22,0x3f4ebef1,
0x3f2cbf7b,0xbf7d3f55,0x3f71bf0e,0x3f78bf7b,0xbf04bdc9,0xbf3e3f75,0x3f18bf75,0x3edbbf46,0xbf7d3f35,0x3f71bf35,0xbe79bec4,0xbf803f6d,
0xbedb3f62,0x3f5cbf7f,0xbf803f46,0xbf183f62,0x3f3ebe48,0x3e16bf0e,0xbeac3f55,0x3e793e48,0x3f5cbf7f,0xbf2c3e95,0x3f4ebe95,0x3f67bf22,
0xbf353f80,0xbf553f80,0xbf353f80,0xbf0e0000,0x3f350000,0x3e483ec4,0x3f350000,0xbf7b3f6d,0x3f35bf80,0x3f7bbf35,0x3f35bf80,0xbe483f35,
0xbf350000,0x3f0ebf6d,0xbf350000,0x3f55bec4,0xbf350000,0xbf0e0000,0xbf350000,0x3f55bf80,0xbf353f80,0xbf7b3f6d,0xbf353f80,0xbe48bec4,
0x3f350000,0xbe483f35,0x3f350000,0xbf7b3f35,0x3f35bf80,0x3f55bec4,0x3f35bf80,0xbf0e3f6d,0x3f2c0000,0x3f040000,0x3eac3ec4,0xbf7d3f6d,
0x3f4ebf7f,0x3f80bf62,0x3f78bf62,0xbeac3f46,0xbf04be48,0x3edbbf55,0xbe16bf0e,0x3f2cbe48,0xbf673f75,0xbf183dc9,0xbf803f46,0x3f78bf75,
0xbf3e3f80,0xbf5c3f80,0xbf713f6d,0xbe16bec4,0x3f183dc9,0x3d493ef1,0x3e793ef1,0xbf713f22,0x3f5cbf7b,0x3f67bf0e,0x3f7dbf55,0xbf3e3f7b,
0xbedbbe95,0x3f4ebf7f,0xbd49bf22,0x3e793e95,0x3f46bf80,0x3f62bf80,0x3f7fbf35,0xbe953f35,0xbef1be48,0x3dc9bf0e,0x3e95bf55,0x3f22be48,
0xbf753f6d,0xbf463ec4,0xbf623ec4,0x3f7fbf6d,0x3dc93f0e,0xbf753f7b,0xbf223f7b,0x3ef1bf55,0x3f220000,0x3ef10000,0xbdc93f35,0xbf753f35,
0x3f62bf7b,0x3f7fbf55,0x3f75bf0e,0xbf463f7b,0xbe95bec4,0x3f22bf6d,0x3ef1bf6d,0x3dc93ec4,0xbf7f3f55,0xbe95be48,0xbf463e48,0x3f62bf0e,
0xbf180000,0xbedb0000,0x3f04bf6d,0x3f3ebec4,0xbf713f75,0xbf783f46,0xbf2c3dc9,0x3f7dbf75,0x3d493f0e,0xbf4e3f7b,0xbf673f7b,0x3f04bf55,
0x3f78bf22,0xbd493ef1,0x3e163ef1,0xbeacbdc9,0x3f4ebf80,0x3f67bf80,0x3f5cbec4,0xbf2c3f6d,0xbeacbe95,0x3e79bf22,0x3f3ebf7f,0x3e163e95,
0xbf803f55,0xbf183e48,0xbedbbe48,0x3f5cbf0e,0xbe793f46,0xbf803f62,0xbf7d3f62,0x3f71bf7f,0xbf353f80,0x3f55bf80,0xbf353f80,0x3f0e0000,
0x3f350000,0xbe48bec4,0x3f350000,0x3f7bbf6d,0x3f35bf80,0xbf7b3f35,0x3f35bf80,0x3e48bf35,0xbf350000,0xbf0e3f6d,0xbf350000,0xbf553ec4,
0xbf350000,0x3f0e0000,0xbf350000,0xbf553f80,0xbf353f80,0x3f7bbf6d,0xbf353f80,0x3e483ec4,0x3f350000,0x3e48bf35,0x3f350000,0x3f7bbf35,
0x3f35bf80,0xbf553ec4,0x3f35bf80,0x3f0ebf6d,0xbd493f35,0x3e79bf35,0xbedb3f6d,0x3f4ebec4,0x3f7dbf22,0xbf3e3e95,0x3f5cbe95,0x3f67bf7f,
0x3e79bf55,0xbf713f7b,0x3f18bf7b,0x3d49bf0e,0xbf713ef1,0xbe163f22,0xbf3e3dc9,0xbf5c3ef1,0xbf803f35,0x3f78bf35,0xbf673ec4,0xbf183f6d,
0xbe163f46,0x3f2cbf75,0xbf043f75,0x3edb3dc9,0x3f78bf0e,0xbeacbe48,0x3f4ebe48,0x3f80bf55,0x3eacbf62,0xbf7d3f46,0x3f2cbf7f,0x3f04bf62,
0x3f220000,0xbef10000,0xbdc93f35,0x3f75bf35,0x3f62bf7b,0xbf7f3f55,0x3f75bf0e,0x3f46bf7b,0xbe95bec4,0xbf223f6d,0x3ef1bf6d,0xbdc9bec4,
0xbf7f3f55,0x3e953e48,0xbf463e48,0xbf623f0e,0xbf463f80,0x3f62bf80,0xbf7f3f35,0xbe953f35,0x3ef13e48,0x3dc9bf0e,0xbe953f55,0x3f22be48,
0x3f75bf6d,0xbf463ec4,0x3f62bec4,0x3f7fbf6d,0xbdc9bf0e,0xbf753f7b,0x3f22bf7b,0x3ef1bf55,0x3f7dbf35,0xbf713f35,0x3e793ec4,0x3f80bf6d,
0x3edbbf62,0xbf5c3f7f,0x3f80bf46,0x3f18bf62,0xbf3e3e48,0xbe163f0e,0x3eacbf55,0xbe79be48,0xbf5c3f7f,0x3f2cbe95,0xbf4e3e95,0xbf673f22,
0xbe163f35,0x3eacbf35,0xbf783f6d,0x3d493ec4,0x3f67bef1,0xbf043dc9,0xbd493f22,0x3f4ebef1,0x3f2cbf7b,0xbf7d3f55,0x3f71bf0e,0x3f78bf7b,
0xbf04bdc9,0xbf3e3f75,0x3f18bf75,0x3edbbf46,0xbf6d3f80,0xbf7b3f80,0x3f6dbf80,0x3e480000,0xbec43f35,0xbf553f6d,0x3ec4bf35,0x3f0ebec4,
0x3ec40000,0xbf0e3f35,0xbec40000,0x3f55bf35,0x3f6dbf35,0xbe483ec4,0xbf6d3f35,0x3f7bbf6d,0xbec40000,0xbe480000,0x3ec40000,0xbf7b3f80,
0xbf6d3f35,0xbf0e3ec4,0x3f6dbf35,0xbf553f6d,0xbf6d3f80,0xbf553f35,0x3f6dbf80,0xbf0e3f35,0xbec43f35,0xbf7b3f6d,0x3ec4bf35,0xbe483ec4,
0xbf713f80,0xbf7d3f80,0x3f80bf6d,0xbe793ec4,0xbf043f46,0xbf673f75,0x3f4ebf75,0x3d493dc9,0x3e163e48,0xbf3e3f55,0x3e79bf0e,0x3eacbe48,
0x3f3ebef1,0xbf043f22,0xbedb3dc9,0x3f18bef1,0xbeac0000,0xbe160000,0xbd493ec4,0xbf783f6d,0xbf5c3f22,0xbedb3e95,0x3f18be95,0xbf803f7f,
0xbf7d3f7b,0xbf2c3f0e,0x3f78bf55,0xbf713f7b,0xbf2c3f62,0xbf5c3f46,0x3f67bf7f,0xbf4e3f62,0xbf753f80,0xbf7f3f80,0x3f62bf35,0xbf223f35,
0xbf223f55,0xbf753f7b,0x3f7fbf7b,0xbef13f0e,0xbdc93ec4,0xbf623f6d,0x3f46bf6d,0xbe953ec4,0x3ef1be48,0xbf463f55,0x3e95bf0e,0xbdc93e48,
0xbe950000,0xbdc90000,0xbef13f35,0xbf463f35,0xbf463f0e,0xbe953e48,0x3dc93e48,0xbf623f55,0xbf7f3f6d,0xbef13ec4,0x3f22bec4,0xbf753f6d,
0xbf623f7b,0xbf223f0e,0x3f75bf55,0xbf7f3f7b,0xbf783f80,0xbf803f80,0x3f18bec4,0xbf673f6d,0xbf3e3f62,0xbf7d3f7f,0x3f67bf46,0xbf5c3f62,
0xbeac3f0e,0xbf783f7b,0x3f80bf7b,0xbf4e3f55,0x3e163dc9,0xbf713f75,0x3f5cbf75,0xbf3e3f46,0xbe790000,0xbd490000,0xbf4e3f6d,0xbedb3ec4,
0xbf2c3ef1,0xbe163dc9,0xbedb3f22,0xbf043ef1,0xbf713f55,0xbe793e48,0x3d493e48,0xbf183f0e,0xbf7d3f7f,0xbeac3e95,0x3f04be95,0xbf2c3f22,
0xbf6d3f80,0x3f7bbf80,0x3f6dbf80,0xbe480000,0xbec43f35,0x3f55bf6d,0x3ec4bf35,0xbf0e3ec4,0x3ec40000,0x3f0ebf35,0xbec40000,0xbf553f35,
0x3f6dbf35,0x3e48bec4,0xbf6d3f35,0xbf7b3f6d,0xbec40000,0x3e480000,0x3ec40000,0x3f7bbf80,0xbf6d3f35,0x3f0ebec4,0x3f6dbf35,0x3f55bf6d,
0xbf6d3f80,0x3f55bf35,0x3f6dbf80,0x3f0ebf35,0xbec43f35,0x3f7bbf6d,0x3ec4bf35,0x3e48bec4,0xbf673f35,0x3f4ebf35,0x3f2cbec4,0x3f5cbf6d,
0xbf783f7f,0x3f71bf62,0x3f7dbf62,0x3f2cbf46,0xbf183f55,0x3f80bf7b,0x3f5cbf7b,0x3edbbf0e,0x3d493e95,0x3f78bf7f,0x3eacbf22,0x3e16be95,
0x3edbbf35,0xbf183f35,0xbf3e3f6d,0x3f04bec4,0xbe79bdc9,0xbeac3ef1,0xbe163ef1,0x3f3ebf22,0xbf4e3f0e,0xbd493e48,0x3f04be48,0x3f67bf55,
0xbf803f75,0x3e79bdc9,0x3f71bf46,0x3f7dbf75,0xbe950000,0x3dc90000,0xbef13f35,0x3f46bf35,0xbf463f0e,0x3e95be48,0x3dc93e48,0x3f62bf55,
0xbf7f3f6d,0x3ef1bec4,0x3f22bec4,0x3f75bf6d,0xbf623f7b,0x3f22bf0e,0x3f75bf55,0x3f7fbf7b,0x3f75bf80,0xbf7f3f80,0xbf623f35,0xbf223f35,
0x3f22bf55,0xbf753f7b,0xbf7f3f7b,0xbef13f0e,0x3dc9bec4,0xbf623f6d,0xbf463f6d,0xbe953ec4,0xbef13e48,0xbf463f55,0xbe953f0e,0xbdc93e48,
0x3f04bf35,0xbf2c3f35,0xbf7d3f6d,0xbeac3ec4,0x3d49be95,0xbf183f22,0xbf713f7f,0xbe793e95,0xbedb3e48,0xbf043f0e,0xbf2c3f55,0xbe163e48,
0xbf4e3f22,0xbedb3ef1,0xbe793ef1,0xbd493dc9,0x3f5cbf35,0xbf3e3f35,0x3e16bec4,0xbf713f6d,0x3f80bf75,0xbf4e3f46,0xbeac3dc9,0xbf783f75,
0x3f67bf7b,0xbf5c3f55,0xbf3e3f0e,0xbf7d3f7b,0x3f18bf46,0xbf673f62,0xbf783f62,0xbf803f7f,0xbf6d3f80,0xbf7b3f80,0x3f6dbf80,0x3e480000,
0xbec43f35,0xbf553f6d,0x3ec4bf35,0x3f0ebec4,0x3ec40000,0xbf0e3f35,0xbec40000,0x3f55bf35,0x3f6dbf35,0xbe483ec4,0xbf6d3f35,0x3f7bbf6d,
0xbec40000,0xbe480000,0x3ec40000,0xbf7b3f80,0xbf6d3f35,0xbf0e3ec4,0x3f6dbf35,0xbf553f6d,0xbf6d3f80,0xbf553f35,0x3f6dbf80,0xbf0e3f35,
0xbec43f35,0xbf7b3f6d,0x3ec4bf35,0xbe483ec4,0xbeac0000,0xbe160000,0xbd493ec4,0xbf783f6d,0xbf5c3f22,0xbedb3e95,0x3f18be95,0xbf803f7f,
0xbf7d3f7b,0xbf2c3f0e,0x3f78bf55,0xbf713f7b,0xbf2c3f62,0xbf5c3f46,0x3f67bf7f,0xbf4e3f62,0x3f71bf80,0x3f7dbf80,0xbf803f6d,0x3e79bec4,
0x3f04bf46,0x3f67bf75,0xbf4e3f75,0xbd49bdc9,0xbe16be48,0x3f3ebf55,0xbe793f0e,0xbeac3e48,0xbf3e3ef1,0x3f04bf22,0x3edbbdc9,0xbf183ef1,
0x3f75bf80,0x3f7fbf80,0xbf623f35,0x3f22bf35,0x3f22bf55,0x3f75bf7b,0xbf7f3f7b,0x3ef1bf0e,0x3dc9bec4,0x3f62bf6d,0xbf463f6d,0x3e95bec4,
0xbef13e48,0x3f46bf55,0xbe953f0e,0x3dc9be48,0x3e950000,0x3dc90000,0x3ef1bf35,0x3f46bf35,0x3f46bf0e,0x3e95be48,0xbdc9be48,0x3f62bf55,
0x3f7fbf6d,0x3ef1bec4,0xbf223ec4,0x3f75bf6d,0x3f62bf7b,0x3f22bf0e,0xbf753f55,0x3f7fbf7b,0x3e790000,0x3d490000,0x3f4ebf6d,0x3edbbec4,
0x3f2cbef1,0x3e16bdc9,0x3edbbf22,0x3f04bef1,0x3f71bf55,0x3e79be48,0xbd49be48,0x3f18bf0e,0x3f7dbf7f,0x3eacbe95,0xbf043e95,0x3f2cbf22,
0xbf783f80,0xbf803f80,0x3f18bec4,0xbf673f6d,0xbf3e3f62,0xbf7d3f7f,0x3f67bf46,0xbf5c3f62,0xbeac3f0e,0xbf783f7b,0x3f80bf7b,0xbf4e3f55,
0x3e163dc9,0xbf713f75,0x3f5cbf75,0xbf3e3f46,0xbf6d3f80,0x3f7bbf80,0x3f6dbf80,0xbe480000,0xbec43f35,0x3f55bf6d,0x3ec4bf35,0xbf0e3ec4,
0x3ec40000,0x3f0ebf35,0xbec40000,0xbf553f35,0x3f6dbf35,0x3e48bec4,0xbf6d3f35,0xbf7b3f6d,0xbec40000,0x3e480000,0x3ec40000,0x3f7bbf80,
0xbf6d3f35,0x3f0ebec4,0x3f6dbf35,0x3f55bf6d,0xbf6d3f80,0x3f55bf35,0x3f6dbf80,0x3f0ebf35,0xbec43f35,0x3f7bbf6d,0x3ec4bf35,0x3e48bec4,
0x3edbbf35,0xbf183f35,0xbf3e3f6d,0x3f04bec4,0xbe79bdc9,0xbeac3ef1,0xbe163ef1,0x3f3ebf22,0xbf4e3f0e,0xbd493e48,0x3f04be48,0x3f67bf55,
0xbf803f75,0x3e79bdc9,0x3f71bf46,0x3f7dbf75,0x3f67bf35,0xbf4e3f35,0xbf2c3ec4,0xbf5c3f6d,0x3f78bf7f,0xbf713f62,0xbf7d3f62,0xbf2c3f46,
0x3f18bf55,0xbf803f7b,0xbf5c3f7b,0xbedb3f0e,0xbd49be95,0xbf783f7f,0xbeac3f22,0xbe163e95,0x3e950000,0xbdc90000,0x3ef1bf35,0xbf463f35,
0x3f46bf0e,0xbe953e48,0xbdc9be48,0xbf623f55,0x3f7fbf6d,0xbef13ec4,0xbf223ec4,0xbf753f6d,0x3f62bf7b,0xbf223f0e,0xbf753f55,0xbf7f3f7b,
0xbf753f80,0x3f7fbf80,0x3f62bf35,0x3f22bf35,0xbf223f55,0x3f75bf7b,0x3f7fbf7b,0x3ef1bf0e,0xbdc93ec4,0x3f62bf6d,0x3f46bf6d,0x3e95bec4,
0x3ef1be48,0x3f46bf55,0x3e95bf0e,0x3dc9be48,0xbf5c3f35,0x3f3ebf35,0xbe163ec4,0x3f71bf6d,0xbf803f75,0x3f4ebf46,0x3eacbdc9,0x3f78bf75,
0xbf673f7b,0x3f5cbf55,0x3f3ebf0e,0x3f7dbf7b,0xbf183f46,0x3f67bf62,0x3f78bf62,0x3f80bf7f,0x3f04bf35,0xbf2c3f35,0xbf7d3f6d,0xbeac3ec4,
0x3d49be95,0xbf183f22,0xbf713f7f,0xbe793e95,0xbedb3e48,0xbf043f0e,0xbf2c3f55,0xbe163e48,0xbf4e3f22,0xbedb3ef1,0xbe793ef1,0xbd493dc9,
0xbf6d3f80,0xbf7b3f80,0x3f6dbf80,0x3e480000,0xbec43f35,0xbf553f6d,0x3ec4bf35,0x3f0ebec4,0x3ec40000,0xbf0e3f35,0xbec40000,0x3f55bf35,
0x3f6dbf35,0xbe483ec4,0xbf6d3f35,0x3f7bbf6d,0xbec40000,0xbe480000,0x3ec40000,0xbf7b3f80,0xbf6d3f35,0xbf0e3ec4,0x3f6dbf35,0xbf553f6d,
0xbf6d3f80,0xbf553f35,0x3f6dbf80,0xbf0e3f35,0xbec43f35,0xbf7b3f6d,0x3ec4bf35,0xbe483ec4,0x3f71bf80,0x3f7dbf80,0xbf803f6d,0x3e79bec4,
0x3f04bf46,0x3f67bf75,0xbf4e3f75,0xbd49bdc9,0xbe16be48,0x3f3ebf55,0xbe793f0e,0xbeac3e48,0xbf3e3ef1,0x3f04bf22,0x3edbbdc9,0xbf183ef1,
0x3eac0000,0x3e160000,0x3d49bec4,0x3f78bf6d,0x3f5cbf22,0x3edbbe95,0xbf183e95,0x3f80bf7f,0x3f7dbf7b,0x3f2cbf0e,0xbf783f55,0x3f71bf7b,
0x3f2cbf62,0x3f5cbf46,0xbf673f7f,0x3f4ebf62,0xbf753f80,0xbf7f3f80,0x3f62bf35,0xbf223f35,0xbf223f55,0xbf753f7b,0x3f7fbf7b,0xbef13f0e,
0xbdc93ec4,0xbf623f6d,0x3f46bf6d,0xbe953ec4,0x3ef1be48,0xbf463f55,0x3e95bf0e,0xbdc93e48,0xbe950000,0xbdc90000,0xbef13f35,0xbf463f35,
0xbf463f0e,0xbe953e48,0x3dc93e48,0xbf623f55,0xbf7f3f6d,0xbef13ec4,0x3f22bec4,0xbf753f6d,0xbf623f7b,0xbf223f0e,0x3f75bf55,0xbf7f3f7b,
0x3f78bf80,0x3f80bf80,0xbf183ec4,0x3f67bf6d,0x3f3ebf62,0x3f7dbf7f,0xbf673f46,0x3f5cbf62,0x3eacbf0e,0x3f78bf7b,0xbf803f7b,0x3f4ebf55,
0xbe16bdc9,0x3f71bf75,0xbf5c3f75,0x3f3ebf46,0x3e790000,0x3d490000,0x3f4ebf6d,0x3edbbec4,0x3f2cbef1,0x3e16bdc9,0x3edbbf22,0x3f04bef1,
0x3f71bf55,0x3e79be48,0xbd49be48,0x3f18bf0e,0x3f7dbf7f,0x3eacbe95,0xbf043e95,0x3f2cbf22,0xbf6d3f80,0x3f7bbf80,0x3f6dbf80,0xbe480000,
0xbec43f35,0x3f55bf6d,0x3ec4bf35,0xbf0e3ec4,0x3ec40000,0x3f0ebf35,0xbec40000,0xbf553f35,0x3f6dbf35,0x3e48bec4,0xbf6d3f35,0xbf7b3f6d,
0xbec40000,0x3e480000,0x3ec40000,0x3f7bbf80,0xbf6d3f35,0x3f0ebec4,0x3f6dbf35,0x3f55bf6d,0xbf6d3f80,0x3f55bf35,0x3f6dbf80,0x3f0ebf35,
0xbec43f35,0x3f7bbf6d,0x3ec4bf35,0x3e48bec4,0x3f67bf35,0xbf4e3f35,0xbf2c3ec4,0xbf5c3f6d,0x3f78bf7f,0xbf713f62,0xbf7d3f62,0xbf2c3f46,
0x3f18bf55,0xbf803f7b,0xbf5c3f7b,0xbedb3f0e,0xbd49be95,0xbf783f7f,0xbeac3f22,0xbe163e95,0xbedb3f35,0x3f18bf35,0x3f3ebf6d,0xbf043ec4,
0x3e793dc9,0x3eacbef1,0x3e16bef1,0xbf3e3f22,0x3f4ebf0e,0x3d49be48,0xbf043e48,0xbf673f55,0x3f80bf75,0xbe793dc9,0xbf713f46,0xbf7d3f75,
0xbe950000,0x3dc90000,0xbef13f35,0x3f46bf35,0xbf463f0e,0x3e95be48,0x3dc93e48,0x3f62bf55,0xbf7f3f6d,0x3ef1bec4,0x3f22bec4,0x3f75bf6d,
0xbf623f7b,0x3f22bf0e,0x3f75bf55,0x3f7fbf7b,0x3f75bf80,0xbf7f3f80,0xbf623f35,0xbf223f35,0x3f22bf55,0xbf753f7b,0xbf7f3f7b,0xbef13f0e,
0x3dc9bec4,0xbf623f6d,0xbf463f6d,0xbe953ec4,0xbef13e48,0xbf463f55,0xbe953f0e,0xbdc93e48,0xbf043f35,0x3f2cbf35,0x3f7dbf6d,0x3eacbec4,
0xbd493e95,0x3f18bf22,0x3f71bf7f,0x3e79be95,0x3edbbe48,0x3f04bf0e,0x3f2cbf55,0x3e16be48,0x3f4ebf22,0x3edbbef1,0x3e79bef1,0x3d49bdc9,
0xbf5c3f35,0x3f3ebf35,0xbe163ec4,0x3f71bf6d,0xbf803f75,0x3f4ebf46,0x3eacbdc9,0x3f78bf75,0xbf673f7b,0x3f5cbf55,0x3f3ebf0e,0x3f7dbf7b,
0xbf183f46,0x3f67bf62,0x3f78bf62,0x3f80bf7f,0xbf6d3f80,0xbf7b3f80,0x3f6dbf80,0x3e480000,0xbec43f35,0xbf553f6d,0x3ec4bf35,0x3f0ebec4,
0x3ec40000,0xbf0e3f35,0xbec40000,0x3f55bf35,0x3f6dbf35,0xbe483ec4,0xbf6d3f35,0x3f7bbf6d,0xbec40000,0xbe480000,0x3ec40000,0xbf7b3f80,
0xbf6d3f35,0xbf0e3ec4,0x3f6dbf35,0xbf553f6d,0xbf6d3f80,0xbf553f35,0x3f6dbf80,0xbf0e3f35,0xbec43f35,0xbf7b3f6d,0x3ec4bf35,0xbe483ec4,
0x3eac0000,0x3e160000,0x3d49bec4,0x3f78bf6d,0x3f5cbf22,0x3edbbe95,0xbf183e95,0x3f80bf7f,0x3f7dbf7b,0x3f2cbf0e,0xbf783f55,0x3f71bf7b,
0x3f2cbf62,0x3f5cbf46,0xbf673f7f,0x3f4ebf62,0xbf713f80,0xbf7d3f80,0x3f80bf6d,0xbe793ec4,0xbf043f46,0xbf673f75,0x3f4ebf75,0x3d493dc9,
0x3e163e48,0xbf3e3f55,0x3e79bf0e,0x3eacbe48,0x3f3ebef1,0xbf043f22,0xbedb3dc9,0x3f18bef1,0x3f75bf80,0x3f7fbf80,0xbf623f35,0x3f22bf35,
0x3f22bf55,0x3f75bf7b,0xbf7f3f7b,0x3ef1bf0e,0x3dc9bec4,0x3f62bf6d,0xbf463f6d,0x3e95bec4,0xbef13e48,0x3f46bf55,0xbe953f0e,0x3dc9be48,
0x3e950000,0x3dc90000,0x3ef1bf35,0x3f46bf35,0x3f46bf0e,0x3e95be48,0xbdc9be48,0x3f62bf55,0x3f7fbf6d,0x3ef1bec4,0xbf223ec4,0x3f75bf6d,
0x3f62bf7b,0x3f22bf0e,0xbf753f55,0x3f7fbf7b,0xbe790000,0xbd490000,0xbf4e3f6d,0xbedb3ec4,0xbf2c3ef1,0xbe163dc9,0xbedb3f22,0xbf043ef1,
0xbf713f55,0xbe793e48,0x3d493e48,0xbf183f0e,0xbf7d3f7f,0xbeac3e95,0x3f04be95,0xbf2c3f22,0x3f78bf80,0x3f80bf80,0xbf183ec4,0x3f67bf6d,
0x3f3ebf62,0x3f7dbf7f,0xbf673f46,0x3f5cbf62,0x3eacbf0e,0x3f78bf7b,0xbf803f7b,0x3f4ebf55,0xbe16bdc9,0x3f71bf75,0xbf5c3f75,0x3f3ebf46,
0xbf6d3f80,0x3f7bbf80,0x3f6dbf80,0xbe480000,0xbec43f35,0x3f55bf6d,0x3ec4bf35,0xbf0e3ec4,0x3ec40000,0x3f0ebf35,0xbec40000,0xbf553f35,
0x3f6dbf35,0x3e48bec4,0xbf6d3f35,0xbf7b3f6d,0xbec40000,0x3e480000,0x3ec40000,0x3f7bbf80,0xbf6d3f35,0x3f0ebec4,0x3f6dbf35,0x3f55bf6d,
0xbf6d3f80,0x3f55bf35,0x3f6dbf80,0x3f0ebf35,0xbec43f35,0x3f7bbf6d,0x3ec4bf35,0x3e48bec4,0xbedb3f35,0x3f18bf35,0x3f3ebf6d,0xbf043ec4,
0x3e793dc9,0x3eacbef1,0x3e16bef1,0xbf3e3f22,0x3f4ebf0e,0x3d49be48,0xbf043e48,0xbf673f55,0x3f80bf75,0xbe793dc9,0xbf713f46,0xbf7d3f75,
0xbf673f35,0x3f4ebf35,0x3f2cbec4,0x3f5cbf6d,0xbf783f7f,0x3f71bf62,0x3f7dbf62,0x3f2cbf46,0xbf183f55,0x3f80bf7b,0x3f5cbf7b,0x3edbbf0e,
0x3d493e95,0x3f78bf7f,0x3eacbf22,0x3e16be95,0x3e950000,0xbdc90000,0x3ef1bf35,0xbf463f35,0x3f46bf0e,0xbe953e48,0xbdc9be48,0xbf623f55,
0x3f7fbf6d,0xbef13ec4,0xbf223ec4,0xbf753f6d,0x3f62bf7b,0xbf223f0e,0xbf753f55,0xbf7f3f7b,0xbf753f80,0x3f7fbf80,0x3f62bf35,0x3f22bf35,
0xbf223f55,0x3f75bf7b,0x3f7fbf7b,0x3ef1bf0e,0xbdc93ec4,0x3f62bf6d,0x3f46bf6d,0x3e95bec4,0x3ef1be48,0x3f46bf55,0x3e95bf0e,0x3dc9be48,
0x3f5cbf35,0xbf3e3f35,0x3e16bec4,0xbf713f6d,0x3f80bf75,0xbf4e3f46,0xbeac3dc9,0xbf783f75,0x3f67bf7b,0xbf5c3f55,0xbf3e3f0e,0xbf7d3f7b,
0x3f18bf46,0xbf673f62,0xbf783f62,0xbf803f7f,0xbf043f35,0x3f2cbf35,0x3f7dbf6d,0x3eacbec4,0xbd493e95,0x3f18bf22,0x3f71bf7f,0x3e79be95,
0x3edbbe48,0x3f04bf0e,0x3f2cbf55,0x3e16be48,0x3f4ebf22,0x3edbbef1,0x3e79bef1,0x3d49bdc9,
};
alignas(128) __device__ const uint32_t T_G128[8192] = {
0x3f803f80,0x3f803f80,0x4000,0xc0000000,0x4000,0xbf443fed,0x4000,0xbfedbf44,0x4000,0xbfb53fb5,0x4000,0xbfb5bfb5,
0x4000,0xbfed3f44,0x4000,0xbf44bfed,0xbf803f80,0xbf803f80,0xbec83ffb,0xbffbbec8,0xbdc94000,0xbf5b3fe7,0xbef93ff8,0xbfcebf98,
0xbe493fff,0xbfc63fa2,0xbf153ff5,0xbf71bfe2,0xbe963ffd,0xbff83ef9,0xbf2c3ff1,0xbdc9c000,0x3f803f80,0x3f803f80,0xbf443fed,0xbfedbf44,
0xbe493fff,0xbf713fe2,0xbf713fe2,0xbfa2bfc6,0xbec83ffb,0xbfd53f8e,0xbf8e3fd5,0xbec8bffb,0xbf153ff5,0xbfff3e49,0xbfa23fc6,0x3f15bff5,
0xbf803f80,0xbf803f80,0xbf8e3fd5,0xbfd5bf8e,0xbe963ffd,0xbf843fdc,0xbfac3fbe,0xbf5bbfe7,0xbf153ff5,0xbfe23f71,0xbfc63fa2,0x3e49bfff,
0xbf5b3fe7,0xc000bdc9,0xbfdc3f84,0x3f98bfce,0x3f803f80,0x3f803f80,0xbfb53fb5,0xbfb5bfb5,0xbec83ffb,0xbf8e3fd5,0xbfd53f8e,0xbec8bffb,
0xbf443fed,0xbfed3f44,0xbfed3f44,0x3f44bfed,0xbf8e3fd5,0xbffbbec8,0xbffb3ec8,0x3fd5bf8e,0xbf803f80,0xbf803f80,0xbfd53f8e,0xbf8ebfd5,
0xbef93ff8,0xbf983fce,0xbff13f2c,0x3dc9c000,0xbf713fe2,0xbff53f15,0xbfff3e49,0x3fa2bfc6,0xbfac3fbe,0xbff1bf2c,0xbffdbe96,0x3ff8bef9,
0x3f803f80,0x3f803f80,0xbfed3f44,0xbf44bfed,0xbf153ff5,0xbfa23fc6,0xbfff3e49,0x3f15bff5,0xbf8e3fd5,0xbffb3ec8,0xbffbbec8,0x3fd5bf8e,
0xbfc63fa2,0xbfe2bf71,0xbfe2bf71,0x3fff3e49,0xbf803f80,0xbf803f80,0xbffb3ec8,0xbec8bffb,0xbf2c3ff1,0xbfac3fbe,0xbffdbe96,0x3f84bfdc,
0xbfa23fc6,0xbfff3e49,0xbfe2bf71,0x3ff5bf15,0xbfdc3f84,0xbfcebf98,0xbfacbfbe,0x3fe73f5b,0x4000,0xc000,0x4000,0x40000000,
0x4000,0x3f44bfed,0x4000,0x3fed3f44,0x4000,0x3fb5bfb5,0x4000,0x3fb53fb5,0x4000,0x3fedbf44,0x4000,0x3f443fed,
0xbf443fed,0x3f44bfed,0xbf8e3fd5,0x3fd53f8e,0xbf5b3fe7,0x3fbebfac,0xbf983fce,0x3f843fdc,0xbf713fe2,0x3ff5bf15,0xbfa23fc6,0x3e493fff,
0xbf843fdc,0x3ffd3e96,0xbfac3fbe,0xbf2c3ff1,0xbfb53fb5,0x3fb5bfb5,0xbfed3f44,0x3f443fed,0xbfc63fa2,0x3ff5bf15,0xbff53f15,0xbe493fff,
0xbfd53f8e,0x3ffb3ec8,0xbffb3ec8,0xbf8e3fd5,0xbfe23f71,0x3fc63fa2,0xbfff3e49,0xbfe23f71,0xbfed3f44,0x3fedbf44,0xbffbbec8,0xbec83ffb,
0xbff83ef9,0x3ffd3e96,0xbff1bf2c,0xbfac3fbe,0xbfff3e49,0x3fc63fa2,0xbfe2bf71,0xbff53f15,0xc000bdc9,0x3f2c3ff1,0xbfcebf98,0xbff8bef9,
0xc0000000,0x40000000,0xbfb5bfb5,0xbfb53fb5,0xbffbbec8,0x3fd53f8e,0xbf8ebfd5,0xbffb3ec8,0xbfedbf44,0x3f443fed,0xbf44bfed,0xbfedbf44,
0xbfd5bf8e,0xbec83ffb,0xbec8bffb,0xbf8ebfd5,0xbfedbf44,0x3fed3f44,0xbec8bffb,0xbffb3ec8,0xbfcebf98,0x3f843fdc,0x3dc9c000,0xbfe7bf5b,
0xbfa2bfc6,0xbe493fff,0x3f15bff5,0xbf71bfe2,0xbf5bbfe7,0xbfac3fbe,0x3f84bfdc,0x3e96bffd,0xbfb5bfb5,0x3fb53fb5,0x3f44bfed,0xbfedbf44,
0xbf71bfe2,0x3e493fff,0x3fa2bfc6,0xbf71bfe2,0xbec8bffb,0xbf8e3fd5,0x3fd5bf8e,0x3ec8bffb,0x3e49bfff,0xbff53f15,0x3ff5bf15,0x3fc6bfa2,
0xbf44bfed,0x3f443fed,0x3fd5bf8e,0xbf8ebfd5,0xbdc9c000,0xbf2c3ff1,0x3ff8bef9,0x3e96bffd,0x3f15bff5,0xbfe23f71,0x3fff3e49,0x3fc6bfa2,
0x3f98bfce,0xbff8bef9,0x3fe73f5b,0x40003dc9,0x4000,0x4000,0x4000,0xc0000000,0x4000,0xbf443fed,0x4000,0xbfedbf44,
0x4000,0xbfb53fb5,0x4000,0xbfb5bfb5,0x4000,0xbfed3f44,0x4000,0xbf44bfed,0xbfb53fb5,0xbfb53fb5,0xbfd53f8e,0xbf8ebfd5,
0xbfbe3fac,0xbff13f2c,0xbfdc3f84,0xbe96bffd,0xbfc63fa2,0xbfffbe49,0xbfe23f71,0x3f15bff5,0xbfce3f98,0xbfdcbf84,0xbfe73f5b,0x3facbfbe,
0xc0000000,0xc0000000,0xbfedbf44,0x3f44bfed,0xbfffbe49,0xbfe2bf71,0xbfe2bf71,0x3fc6bfa2,0xbffbbec8,0xbf8ebfd5,0xbfd5bf8e,0x3ffbbec8,
0xbff5bf15,0xbe49bfff,0xbfc6bfa2,0x3ff53f15,0xbfb5bfb5,0xbfb5bfb5,0xbec8bffb,0x3ffbbec8,0xbf98bfce,0xbef9bff8,0xbdc9c000,0x3ff13f2c,
0xbf71bfe2,0x3f15bff5,0x3e49bfff,0x3fa23fc6,0xbf2cbff1,0x3fbebfac,0x3ef9bff8,0x3e963ffd,0xc000,0xc000,0x3fb5bfb5,0x3fb53fb5,
0x3ec8bffb,0x3f8ebfd5,0x3fd5bf8e,0x3ec83ffb,0x3f44bfed,0x3fedbf44,0x3fedbf44,0xbf443fed,0x3f8ebfd5,0x3ffb3ec8,0x3ffbbec8,0xbfd53f8e,
0x3fb5bfb5,0x3fb5bfb5,0x3ffb3ec8,0xbec83ffb,0x3fdcbf84,0x3ffdbe96,0x3fe73f5b,0xbfbe3fac,0x3ff5bf15,0x3fe23f71,0x3fc63fa2,0xbfff3e49,
0x4000bdc9,0x3f5b3fe7,0x3f983fce,0xbfdcbf84,0x40000000,0x40000000,0x3f443fed,0xbfed3f44,0x3ff53f15,0x3fc63fa2,0x3e493fff,0xbff5bf15,
0x3fd53f8e,0x3ec83ffb,0xbec83ffb,0xbf8ebfd5,0x3fa23fc6,0xbf713fe2,0xbf713fe2,0x3e49bfff,0x3fb53fb5,0x3fb53fb5,0xbf8e3fd5,0xbfd5bf8e,
0x3f5b3fe7,0x3dc94000,0xbfce3f98,0xbef9bff8,0x3e493fff,0xbfa23fc6,0xbff53f15,0x3f71bfe2,0xbef93ff8,0xbffd3e96,0xc000bdc9,0x3ff1bf2c,
0x4000,0xc000,0x4000,0x40000000,0x4000,0x3f44bfed,0x4000,0x3fed3f44,0x4000,0x3fb5bfb5,0x4000,0x3fb53fb5,
0x4000,0x3fedbf44,0x4000,0x3f443fed,0xbfed3f44,0x3fedbf44,0xbffb3ec8,0x3ec83ffb,0xbff13f2c,0x40003dc9,0xbffd3e96,0xbef93ff8,
0xbff53f15,0x3fe23f71,0xbfff3e49,0xbfa23fc6,0xbff83ef9,0x3f983fce,0xc0003dc9,0xbfe73f5b,0xbfb5bfb5,0x3fb53fb5,0xbf44bfed,0xbfed3f44,
0xbfa2bfc6,0x3f153ff5,0xbf15bff5,0xbfffbe49,0xbf8ebfd5,0xbec83ffb,0xbec8bffb,0xbfd5bf8e,0xbf71bfe2,0xbfa23fc6,0xbe49bfff,0xbf71bfe2,
0x3f44bfed,0xbf443fed,0x3fd5bf8e,0xbf8ebfd5,0x3f84bfdc,0xbfce3f98,0x3fe7bf5b,0xbdc9c000,0x3fa2bfc6,0xbfff3e49,0x3ff5bf15,0x3f71bfe2,
0x3fbebfac,0xbfe7bf5b,0x3ffdbe96,0x3fdcbf84,0x40000000,0xc0000000,0x3fb53fb5,0x3fb5bfb5,0x3ffb3ec8,0xbfd5bf8e,0x3f8e3fd5,0x3ffbbec8,
0x3fed3f44,0xbf44bfed,0x3f443fed,0x3fed3f44,0x3fd53f8e,0x3ec8bffb,0x3ec83ffb,0x3f8e3fd5,0x3f443fed,0xbf44bfed,0xbf8e3fd5,0x3fd53f8e,
0x3e963ffd,0x3ef9bff8,0xbfbe3fac,0x3f2c3ff1,0xbe493fff,0x3fc6bfa2,0xbfe23f71,0xbf153ff5,0xbf2c3ff1,0x4000bdc9,0xbff83ef9,0xbfce3f98,
0xbfb53fb5,0x3fb5bfb5,0xbfedbf44,0xbf443fed,0xbfe23f71,0x3fffbe49,0xbfc6bfa2,0xbfe23f71,0xbffb3ec8,0x3fd53f8e,0xbf8ebfd5,0xbffbbec8,
0xbfffbe49,0x3f153ff5,0xbf15bff5,0xbfa2bfc6,0xbfedbf44,0x3fed3f44,0x3ec8bffb,0xbffbbec8,0xbfbebfac,0x3f5b3fe7,0x3f84bfdc,0xbf98bfce,
0xbf71bfe2,0xbf153ff5,0x3fc6bfa2,0x3e49bfff,0xbe96bffd,0xbfdc3f84,0x3ff1bf2c,0x3fbebfac,0x4000,0x4000,0x4000,0xc0000000,
0x4000,0xbf443fed,0x4000,0xbfedbf44,0x4000,0xbfb53fb5,0x4000,0xbfb5bfb5,0x4000,0xbfed3f44,0x4000,0xbf44bfed,
0xc0000000,0xc0000000,0xbffbbec8,0x3ec8bffb,0xc000bdc9,0xbfe7bf5b,0xbff8bef9,0x3f98bfce,0xbfffbe49,0xbfa2bfc6,0xbff5bf15,0x3fe2bf71,
0xbffdbe96,0xbef9bff8,0xbff1bf2c,0x4000bdc9,0xc000,0xc000,0x3f44bfed,0x3fed3f44,0x3e49bfff,0x3f71bfe2,0x3f71bfe2,0x3fa23fc6,
0x3ec8bffb,0x3fd5bf8e,0x3f8ebfd5,0x3ec83ffb,0x3f15bff5,0x3fffbe49,0x3fa2bfc6,0xbf153ff5,0x40000000,0x40000000,0x3fd53f8e,0xbf8e3fd5,
0x3ffd3e96,0x3fdc3f84,0x3fbe3fac,0xbfe73f5b,0x3ff53f15,0x3f713fe2,0x3fa23fc6,0xbfffbe49,0x3fe73f5b,0xbdc94000,0x3f843fdc,0xbfcebf98,
0x4000,0x4000,0xbfb53fb5,0xbfb5bfb5,0xbec83ffb,0xbf8e3fd5,0xbfd53f8e,0xbec8bffb,0xbf443fed,0xbfed3f44,0xbfed3f44,0x3f44bfed,
0xbf8e3fd5,0xbffbbec8,0xbffb3ec8,0x3fd5bf8e,0xc0000000,0xc0000000,0xbf8ebfd5,0x3fd5bf8e,0xbff8bef9,0xbfcebf98,0xbf2cbff1,0x40003dc9,
0xbfe2bf71,0xbf15bff5,0xbe49bfff,0x3fc63fa2,0xbfbebfac,0x3f2cbff1,0x3e96bffd,0x3ef93ff8,0xc000,0xc000,0x3fedbf44,0x3f443fed,
0x3f15bff5,0x3fa2bfc6,0x3fffbe49,0xbf153ff5,0x3f8ebfd5,0x3ffbbec8,0x3ffb3ec8,0xbfd53f8e,0x3fc6bfa2,0x3fe23f71,0x3fe23f71,0xbfffbe49,
0x40000000,0x40000000,0x3ec83ffb,0xbffb3ec8,0x3ff13f2c,0x3fbe3fac,0xbe963ffd,0xbfdcbf84,0x3fc63fa2,0x3e493fff,0xbf713fe2,0xbf15bff5,
0x3f843fdc,0xbf983fce,0xbfbe3fac,0x3f5bbfe7,0x4000,0xc000,0x4000,0x40000000,0x4000,0x3f44bfed,0x4000,0x3fed3f44,
0x4000,0x3fb5bfb5,0x4000,0x3fb53fb5,0x4000,0x3fedbf44,0x4000,0x3f443fed,0xbfedbf44,0x3fed3f44,0xbfd5bf8e,0xbf8e3fd5,
0xbfe7bf5b,0x3fac3fbe,0xbfcebf98,0xbfdc3f84,0xbfe2bf71,0x3f153ff5,0xbfc6bfa2,0xbfff3e49,0xbfdcbf84,0xbe963ffd,0xbfbebfac,0xbff1bf2c,
0x3fb5bfb5,0xbfb53fb5,0x3fedbf44,0xbf44bfed,0x3fc6bfa2,0xbff53f15,0x3ff5bf15,0x3e49bfff,0x3fd5bf8e,0xbffbbec8,0x3ffbbec8,0x3f8ebfd5,
0x3fe2bf71,0xbfc6bfa2,0x3fffbe49,0x3fe2bf71,0x3f443fed,0xbf44bfed,0xbec83ffb,0x3ffb3ec8,0x3ef93ff8,0x3e96bffd,0xbf2c3ff1,0x3fbe3fac,
0x3e493fff,0x3fa2bfc6,0xbf713fe2,0x3f153ff5,0xbdc94000,0x3ff1bf2c,0xbf983fce,0xbef93ff8,0xc0000000,0x40000000,0xbfb5bfb5,0xbfb53fb5,
0xbffbbec8,0x3fd53f8e,0xbf8ebfd5,0xbffb3ec8,0xbfedbf44,0x3f443fed,0xbf44bfed,0xbfedbf44,0xbfd5bf8e,0xbec83ffb,0xbec8bffb,0xbf8ebfd5,
0x3f44bfed,0xbf443fed,0x3ffbbec8,0xbec8bffb,0x3f98bfce,0xbfdc3f84,0x40003dc9,0x3f5bbfe7,0x3fc6bfa2,0xbfffbe49,0x3ff53f15,0x3fe2bf71,
0x3fe7bf5b,0xbfbebfac,0x3fdc3f84,0x3ffd3e96,0x3fb53fb5,0xbfb5bfb5,0xbf443fed,0x3fed3f44,0x3f713fe2,0xbe49bfff,0xbfa23fc6,0x3f713fe2,
0x3ec83ffb,0x3f8ebfd5,0xbfd53f8e,0xbec83ffb,0xbe493fff,0x3ff5bf15,0xbff53f15,0xbfc63fa2,0xbfed3f44,0x3fedbf44,0xbf8ebfd5,0xbfd53f8e,
0xc0003dc9,0x3ff13f2c,0xbef9bff8,0xbffdbe96,0xbff5bf15,0x3f713fe2,0x3e49bfff,0xbfa2bfc6,0xbfcebf98,0xbef93ff8,0x3f5bbfe7,0x3dc9c000,
0x4000,0x4000,0x4000,0xc0000000,0x4000,0xbf443fed,0x4000,0xbfedbf44,0x4000,0xbfb53fb5,0x4000,0xbfb5bfb5,
0x4000,0xbfed3f44,0x4000,0xbf44bfed,0xbfb5bfb5,0xbfb5bfb5,0xbf8ebfd5,0x3fd5bf8e,0xbfacbfbe,0xbf2cbff1,0xbf84bfdc,0x3ffdbe96,
0xbfa2bfc6,0x3e49bfff,0xbf71bfe2,0x3ff53f15,0xbf98bfce,0x3f84bfdc,0xbf5bbfe7,0x3fbe3fac,0x40000000,0x40000000,0x3fed3f44,0xbf443fed,
0x3fff3e49,0x3fe23f71,0x3fe23f71,0xbfc63fa2,0x3ffb3ec8,0x3f8e3fd5,0x3fd53f8e,0xbffb3ec8,0x3ff53f15,0x3e493fff,0x3fc63fa2,0xbff5bf15,
0xbfb53fb5,0xbfb53fb5,0xbffb3ec8,0xbec8bffb,0xbfce3f98,0xbff83ef9,0xc0003dc9,0x3f2cbff1,0xbfe23f71,0xbff5bf15,0xbfffbe49,0x3fc6bfa2,
0xbff13f2c,0xbfacbfbe,0xbff8bef9,0x3ffdbe96,0xc000,0xc000,0x3fb5bfb5,0x3fb53fb5,0x3ec8bffb,0x3f8ebfd5,0x3fd5bf8e,0x3ec83ffb,
0x3f44bfed,0x3fedbf44,0x3fedbf44,0xbf443fed,0x3f8ebfd5,0x3ffb3ec8,0x3ffbbec8,0xbfd53f8e,0x3fb53fb5,0x3fb53fb5,0xbec83ffb,0xbffbbec8,
0x3f843fdc,0x3e963ffd,0xbf5b3fe7,0xbfacbfbe,0x3f153ff5,0xbf713fe2,0xbfa23fc6,0xbe49bfff,0x3dc94000,0xbfe73f5b,0xbfce3f98,0x3f84bfdc,
0xc0000000,0xc0000000,0xbf44bfed,0x3fedbf44,0xbff5bf15,0xbfc6bfa2,0xbe49bfff,0x3ff53f15,0xbfd5bf8e,0xbec8bffb,0x3ec8bffb,0x3f8e3fd5,
0xbfa2bfc6,0x3f71bfe2,0x3f71bfe2,0xbe493fff,0x3fb5bfb5,0x3fb5bfb5,0x3fd53f8e,0xbf8e3fd5,0x3fe7bf5b,0x4000bdc9,0x3f983fce,0xbff83ef9,
0x3fffbe49,0x3fc63fa2,0x3f153ff5,0xbfe2bf71,0x3ff83ef9,0x3e963ffd,0xbdc94000,0xbf2cbff1,0x4000,0xc000,0x4000,0x40000000,
0x4000,0x3f44bfed,0x4000,0x3fed3f44,0x4000,0x3fb5bfb5,0x4000,0x3fb53fb5,0x4000,0x3fedbf44,0x4000,0x3f443fed,
0xbf44bfed,0x3f443fed,0xbec8bffb,0xbffb3ec8,0xbf2cbff1,0xbdc94000,0xbe96bffd,0xbff8bef9,0xbf15bff5,0xbf713fe2,0xbe49bfff,0xbfc6bfa2,
0xbef9bff8,0xbfce3f98,0xbdc9c000,0xbf5bbfe7,0x3fb53fb5,0xbfb5bfb5,0x3f443fed,0x3fedbf44,0x3fa23fc6,0xbf15bff5,0x3f153ff5,0x3fff3e49,
0x3f8e3fd5,0x3ec8bffb,0x3ec83ffb,0x3fd53f8e,0x3f713fe2,0x3fa2bfc6,0x3e493fff,0x3f713fe2,0xbfedbf44,0x3fed3f44,0xbf8ebfd5,0xbfd53f8e,
0xbfdcbf84,0x3f983fce,0xbf5bbfe7,0xc0003dc9,0xbfc6bfa2,0x3e493fff,0xbf15bff5,0xbfe2bf71,0xbfacbfbe,0xbf5b3fe7,0xbe96bffd,0xbf84bfdc,
0x40000000,0xc0000000,0x3fb53fb5,0x3fb5bfb5,0x3ffb3ec8,0xbfd5bf8e,0x3f8e3fd5,0x3ffbbec8,0x3fed3f44,0xbf44bfed,0x3f443fed,0x3fed3f44,
0x3fd53f8e,0x3ec8bffb,0x3ec83ffb,0x3f8e3fd5,0xbfed3f44,0x3fedbf44,0xbfd5bf8e,0xbf8e3fd5,0xbffd3e96,0x3ff83ef9,0xbfacbfbe,0xbff13f2c,
0xbfffbe49,0x3fa23fc6,0xbf71bfe2,0xbff5bf15,0xbff1bf2c,0x3dc94000,0xbef9bff8,0xbf98bfce,0x3fb5bfb5,0xbfb53fb5,0x3fed3f44,0x3f44bfed,
0x3fe2bf71,0xbfff3e49,0x3fc63fa2,0x3fe2bf71,0x3ffbbec8,0xbfd5bf8e,0x3f8e3fd5,0x3ffb3ec8,0x3fff3e49,0xbf15bff5,0x3f153ff5,0x3fa23fc6,
0xbf443fed,0x3f44bfed,0xbffbbec8,0xbec83ffb,0xbfac3fbe,0x3fe7bf5b,0xbfdcbf84,0xbfce3f98,0xbfe23f71,0x3ff53f15,0xbfa2bfc6,0xbfffbe49,
0xbffd3e96,0x3f843fdc,0xbf2cbff1,0xbfacbfbe,0x3f803f80,0x3f803f80,0xc000,0x40000000,0xbfb53fb5,0xbfed3f44,0x3fb5bfb5,0x3f443fed,
0xc0000000,0xbfb5bfb5,0x40000000,0xbfb53fb5,0xbfb5bfb5,0x3f44bfed,0x3fb53fb5,0xbfedbf44,0xbf803f80,0xbf803f80,0x3ec8bffb,0x3ffb3ec8,
0xbfbe3fac,0xbff13f2c,0x3fdcbf84,0x3e963ffd,0xbfffbe49,0xbfa2bfc6,0x3ff53f15,0xbfe23f71,0xbf98bfce,0x3f84bfdc,0x3f5b3fe7,0xbfbebfac,
0x3f803f80,0x3f803f80,0x3f44bfed,0x3fed3f44,0xbfc63fa2,0xbff53f15,0x3ff5bf15,0xbe493fff,0xbffbbec8,0xbf8ebfd5,0x3fd53f8e,0xbffb3ec8,
0xbf71bfe2,0x3fa2bfc6,0x3e493fff,0xbf71bfe2,0xbf803f80,0xbf803f80,0x3f8ebfd5,0x3fd53f8e,0xbfce3f98,0xbff83ef9,0x4000bdc9,0xbf2c3ff1,
0xbff5bf15,0xbf71bfe2,0x3fa23fc6,0xbfffbe49,0xbf2cbff1,0x3fbebfac,0xbef93ff8,0xbe96bffd,0x3f803f80,0x3f803f80,0x3fb5bfb5,0x3fb53fb5,
0xbfd53f8e,0xbffb3ec8,0x3ffb3ec8,0xbf8e3fd5,0xbfedbf44,0xbf44bfed,0x3f443fed,0xbfedbf44,0xbec8bffb,0x3fd5bf8e,0xbf8e3fd5,0x3ec8bffb,
0xbf803f80,0xbf803f80,0x3fd5bf8e,0x3f8e3fd5,0xbfdc3f84,0xbffd3e96,0x3fe73f5b,0xbfbe3fac,0xbfe2bf71,0xbf15bff5,0x3e493fff,0xbfc6bfa2,
0xbdc9c000,0x3fe7bf5b,0xbfce3f98,0x3f84bfdc,0x3f803f80,0x3f803f80,0x3fedbf44,0x3f443fed,0xbfe23f71,0xbfff3e49,0x3fc63fa2,0xbfe23f71,
0xbfd5bf8e,0xbec8bffb,0xbec83ffb,0xbf8ebfd5,0x3e49bfff,0x3ff5bf15,0xbff53f15,0x3fc6bfa2,0xbf803f80,0xbf803f80,0x3ffbbec8,0x3ec83ffb,
0xbfe73f5b,0xc0003dc9,0x3f983fce,0xbff83ef9,0xbfc6bfa2,0xbe49bfff,0xbf713fe2,0xbf15bff5,0x3ef9bff8,0x3ffdbe96,0xc000bdc9,0x3ff1bf2c,
0x4000,0xc000,0xc000,0xc0000000,0xbfb53fb5,0x3fedbf44,0x3fb5bfb5,0xbf44bfed,0xc0000000,0x3fb53fb5,0x40000000,0x3fb5bfb5,
0xbfb5bfb5,0xbf443fed,0x3fb53fb5,0x3fed3f44,0xbf443fed,0x3f44bfed,0x3f8ebfd5,0xbfd5bf8e,0xbff13f2c,0x40003dc9,0x3ffdbe96,0x3ef9bff8,
0xbfe2bf71,0x3f153ff5,0x3fc63fa2,0x3fffbe49,0xbef9bff8,0xbfce3f98,0x3dc94000,0x3f5b3fe7,0xbfb53fb5,0x3fb5bfb5,0x3fedbf44,0xbf44bfed,
0xbfffbe49,0x3fe23f71,0x3fe23f71,0x3fc6bfa2,0xbf8ebfd5,0xbec83ffb,0x3ec83ffb,0x3fd53f8e,0x3f15bff5,0xbfff3e49,0xbfa23fc6,0xbf153ff5,
0xbfed3f44,0x3fedbf44,0x3ffb3ec8,0x3ec8bffb,0xbfdcbf84,0x3f983fce,0x3f5b3fe7,0x4000bdc9,0xbe49bfff,0xbfa23fc6,0xbf713fe2,0x3f153ff5,
0x3fbebfac,0xbfe7bf5b,0xbffd3e96,0xbfdc3f84,0xc0000000,0x40000000,0x3fb53fb5,0x3fb5bfb5,0xbf8ebfd5,0x3ec83ffb,0xbec83ffb,0x3fd53f8e,
0x3f44bfed,0xbfed3f44,0xbfed3f44,0xbf443fed,0x3ffbbec8,0xbf8ebfd5,0xbfd5bf8e,0xbffbbec8,0xbfedbf44,0x3fed3f44,0x3ec83ffb,0x3ffbbec8,
0xbe96bffd,0xbef93ff8,0xbfbe3fac,0x3f2c3ff1,0x3fc6bfa2,0xbfffbe49,0xbff5bf15,0xbfe23f71,0x3ff13f2c,0xbdc9c000,0xbef9bff8,0xbf98bfce,
0xbfb5bfb5,0x3fb53fb5,0xbf443fed,0x3fed3f44,0x3f15bff5,0xbfa23fc6,0xbfff3e49,0xbf153ff5,0x3ffbbec8,0xbfd5bf8e,0xbf8ebfd5,0xbffbbec8,
0x3fa23fc6,0x3f71bfe2,0x3f71bfe2,0x3e49bfff,0xbf44bfed,0x3f443fed,0xbfd53f8e,0x3f8e3fd5,0x3facbfbe,0xbfe73f5b,0xbfdcbf84,0xbfce3f98,
0x3ff53f15,0xbf71bfe2,0x3e49bfff,0xbfa2bfc6,0x3e963ffd,0x3fdcbf84,0x3ff1bf2c,0x3fbebfac,0x4000,0x4000,0xc000,0x40000000,
0xbfb53fb5,0xbfed3f44,0x3fb5bfb5,0x3f443fed,0xc0000000,0xbfb5bfb5,0x40000000,0xbfb53fb5,0xbfb5bfb5,0x3f44bfed,0x3fb53fb5,0xbfedbf44,
0xbfb53fb5,0xbfb53fb5,0x3fd5bf8e,0x3f8e3fd5,0xc000bdc9,0xbfe7bf5b,0x3ff83ef9,0xbf983fce,0xbfa2bfc6,0x3e49bfff,0x3f713fe2,0xbff5bf15,
0x3e96bffd,0x3ff8bef9,0xbf2c3ff1,0xbdc9c000,0xc0000000,0xc0000000,0x3fed3f44,0xbf443fed,0xbfa2bfc6,0xbf15bff5,0x3f153ff5,0xbfffbe49,
0x3ec8bffb,0x3fd5bf8e,0xbf8e3fd5,0xbec8bffb,0x3fe2bf71,0x3fc63fa2,0xbfff3e49,0x3fe2bf71,0xbfb5bfb5,0xbfb5bfb5,0x3ec83ffb,0xbffb3ec8,
0x3e96bffd,0x3f84bfdc,0xbfac3fbe,0xbf5bbfe7,0x3fe2bf71,0x3ff53f15,0xbfffbe49,0x3fc6bfa2,0x3fe73f5b,0xbdc94000,0xbf84bfdc,0x3fce3f98,
0xc000,0xc000,0xbfb53fb5,0xbfb5bfb5,0x3fd5bf8e,0x3ffbbec8,0xbffbbec8,0x3f8ebfd5,0x3fed3f44,0x3f443fed,0xbf44bfed,0x3fed3f44,
0x3ec83ffb,0xbfd53f8e,0x3f8ebfd5,0xbec83ffb,0x3fb5bfb5,0x3fb5bfb5,0xbffbbec8,0x3ec8bffb,0x3ff83ef9,0x3fce3f98,0xbf2cbff1,0x40003dc9,
0x3f153ff5,0xbf713fe2,0x3fa2bfc6,0x3e493fff,0xbfac3fbe,0xbff1bf2c,0x3ffd3e96,0xbff83ef9,0x40000000,0x40000000,0xbf44bfed,0x3fedbf44,
0x3f713fe2,0x3e493fff,0x3fa2bfc6,0x3f713fe2,0xbf8e3fd5,0xbffb3ec8,0x3ffb3ec8,0xbfd53f8e,0xbfffbe49,0xbf15bff5,0x3f153ff5,0xbfa2bfc6,
0x3fb53fb5,0x3fb53fb5,0x3f8ebfd5,0x3fd53f8e,0xbf2c3ff1,0xbfac3fbe,0x3ffd3e96,0xbf843fdc,0xbfff3e49,0xbfc6bfa2,0x3f153ff5,0xbfe2bf71,
0xbf84bfdc,0x3f98bfce,0xbfbe3fac,0x3f5bbfe7,0x4000,0xc000,0xc000,0xc0000000,0xbfb53fb5,0x3fedbf44,0x3fb5bfb5,0xbf44bfed,
0xc0000000,0x3fb53fb5,0x40000000,0x3fb5bfb5,0xbfb5bfb5,0xbf443fed,0x3fb53fb5,0x3fed3f44,0xbfed3f44,0x3fedbf44,0x3ffbbec8,0xbec8bffb,
0xbfe7bf5b,0x3fac3fbe,0x3fce3f98,0x3fdcbf84,0xbf15bff5,0xbf713fe2,0x3e493fff,0x3fc63fa2,0x3f84bfdc,0xbffdbe96,0xbfac3fbe,0xbf2c3ff1,
0xbfb5bfb5,0x3fb53fb5,0x3f443fed,0x3fedbf44,0x3e49bfff,0xbf713fe2,0xbf713fe2,0x3fa23fc6,0x3fd5bf8e,0xbffbbec8,0xbffb3ec8,0xbf8e3fd5,
0x3ff53f15,0xbe49bfff,0xbfc6bfa2,0xbff5bf15,0x3f44bfed,0xbf443fed,0xbfd53f8e,0x3f8e3fd5,0x3ff8bef9,0xbffdbe96,0xbff1bf2c,0xbfac3fbe,
0x3fc63fa2,0xbe49bfff,0xbf15bff5,0xbfe2bf71,0xbdc94000,0x3ff1bf2c,0x3f98bfce,0x3ef9bff8,0x40000000,0xc0000000,0xbfb5bfb5,0xbfb53fb5,
0x3f8e3fd5,0xbec8bffb,0x3ec8bffb,0xbfd5bf8e,0xbf443fed,0x3fedbf44,0x3fedbf44,0x3f44bfed,0xbffb3ec8,0x3f8e3fd5,0x3fd53f8e,0x3ffb3ec8,
0x3f443fed,0xbf44bfed,0x3f8ebfd5,0xbfd5bf8e,0xbf983fce,0x3fdcbf84,0x40003dc9,0x3f5bbfe7,0xbfffbe49,0x3fa23fc6,0x3f713fe2,0x3ff53f15,
0xbf5bbfe7,0xbfac3fbe,0xbf843fdc,0xbe963ffd,0xbfb53fb5,0x3fb5bfb5,0x3fed3f44,0x3f44bfed,0xbff5bf15,0x3fc63fa2,0x3e493fff,0x3ff53f15,
0xbec8bffb,0xbf8e3fd5,0xbfd53f8e,0xbec83ffb,0x3fc6bfa2,0xbfe2bf71,0xbfe2bf71,0xbfffbe49,0xbfedbf44,0x3fed3f44,0xbec83ffb,0x3ffb3ec8,
0xbdc9c000,0xbf2c3ff1,0xbff83ef9,0xbe963ffd,0x3fe2bf71,0xbff5bf15,0xbfa2bfc6,0xbfffbe49,0x3fce3f98,0x3ef9bff8,0x3f5bbfe7,0x3dc9c000,
0x4000,0x4000,0xc000,0x40000000,0xbfb53fb5,0xbfed3f44,0x3fb5bfb5,0x3f443fed,0xc0000000,0xbfb5bfb5,0x40000000,0xbfb53fb5,
0xbfb5bfb5,0x3f44bfed,0x3fb53fb5,0xbfedbf44,0xc0000000,0xc0000000,0x3ffb3ec8,0xbec83ffb,0xbfacbfbe,0xbf2cbff1,0x3f843fdc,0xbffd3e96,
0x3e49bfff,0x3fc6bfa2,0xbf153ff5,0xbf71bfe2,0x3fcebf98,0x3fdc3f84,0xbfe73f5b,0x3facbfbe,0xc000,0xc000,0xbf443fed,0xbfedbf44,
0x3fc6bfa2,0x3ff5bf15,0xbff53f15,0x3e49bfff,0x3ffb3ec8,0x3f8e3fd5,0xbfd5bf8e,0x3ffbbec8,0x3f713fe2,0xbfa23fc6,0xbe49bfff,0x3f713fe2,
0x40000000,0x40000000,0xbfd5bf8e,0x3f8ebfd5,0x3f983fce,0x3ef93ff8,0xbdc9c000,0x3ff13f2c,0xbf153ff5,0xbfe23f71,0x3fc6bfa2,0xbe493fff,
0xbff13f2c,0xbfacbfbe,0x3ff83ef9,0xbffd3e96,0x4000,0x4000,0x3fb5bfb5,0x3fb53fb5,0xbfd53f8e,0xbffb3ec8,0x3ffb3ec8,0xbf8e3fd5,
0xbfedbf44,0xbf44bfed,0x3f443fed,0xbfedbf44,0xbec8bffb,0x3fd5bf8e,0xbf8e3fd5,0x3ec8bffb,0xc0000000,0xc0000000,0x3f8e3fd5,0xbfd53f8e,
0xbf84bfdc,0xbe96bffd,0xbf5b3fe7,0xbfacbfbe,0x3f71bfe2,0x3ff5bf15,0xbfff3e49,0x3fa2bfc6,0x4000bdc9,0x3f5b3fe7,0xbf98bfce,0x3fdc3f84,
0xc000,0xc000,0xbfed3f44,0xbf44bfed,0x3fe2bf71,0x3fffbe49,0xbfc6bfa2,0x3fe2bf71,0x3fd53f8e,0x3ec83ffb,0x3ec8bffb,0x3f8e3fd5,
0xbe493fff,0xbff53f15,0x3ff5bf15,0xbfc63fa2,0x40000000,0x40000000,0xbec8bffb,0x3ffbbec8,0x3f5b3fe7,0x3dc94000,0x3fcebf98,0x3ef93ff8,
0xbfa23fc6,0xbfff3e49,0x3fe23f71,0xbff53f15,0xbff8bef9,0xbe96bffd,0xbdc94000,0xbf2cbff1,0x4000,0xc000,0xc000,0xc0000000,
0xbfb53fb5,0x3fedbf44,0x3fb5bfb5,0xbf44bfed,0xc0000000,0x3fb53fb5,0x40000000,0x3fb5bfb5,0xbfb5bfb5,0xbf443fed,0x3fb53fb5,0x3fed3f44,
0xbfedbf44,0x3fed3f44,0x3fd53f8e,0x3f8ebfd5,0xbf2cbff1,0xbdc94000,0x3e963ffd,0x3ff83ef9,0x3f71bfe2,0xbff53f15,0xbfa23fc6,0x3e493fff,
0x3ff8bef9,0xbf98bfce,0xc0003dc9,0xbfe73f5b,0x3fb5bfb5,0xbfb53fb5,0xbfed3f44,0x3f443fed,0x3fff3e49,0xbfe2bf71,0xbfe2bf71,0xbfc63fa2,
0x3f8e3fd5,0x3ec8bffb,0xbec8bffb,0xbfd5bf8e,0xbf153ff5,0x3fffbe49,0x3fa2bfc6,0x3f15bff5,0x3f443fed,0xbf44bfed,0x3ec8bffb,0xbffbbec8,
0xbf843fdc,0x3fcebf98,0x3fe7bf5b,0xbdc9c000,0xbfff3e49,0x3fc63fa2,0x3fe23f71,0x3ff5bf15,0xbfacbfbe,0xbf5b3fe7,0x3e963ffd,0x3f843fdc,
0xc0000000,0x40000000,0x3fb53fb5,0x3fb5bfb5,0xbf8ebfd5,0x3ec83ffb,0xbec83ffb,0x3fd53f8e,0x3f44bfed,0xbfed3f44,0xbfed3f44,0xbf443fed,
0x3ffbbec8,0xbf8ebfd5,0xbfd5bf8e,0xbffbbec8,0x3f44bfed,0xbf443fed,0xbffb3ec8,0x3ec83ffb,0x3ffdbe96,0xbff8bef9,0xbfacbfbe,0xbff13f2c,
0x3fa23fc6,0x3e49bfff,0x3f15bff5,0xbf71bfe2,0xbf2c3ff1,0x4000bdc9,0x3ff8bef9,0x3fcebf98,0x3fb53fb5,0xbfb5bfb5,0x3f44bfed,0xbfedbf44,
0xbf153ff5,0x3fa2bfc6,0x3fffbe49,0x3f15bff5,0xbffb3ec8,0x3fd53f8e,0x3f8e3fd5,0x3ffb3ec8,0xbfa2bfc6,0xbf713fe2,0xbf713fe2,0xbe493fff,
0xbfed3f44,0x3fedbf44,0x3f8e3fd5,0x3fd5bf8e,0xbfbebfac,0x3f5b3fe7,0xbf843fdc,0x3f983fce,0x3f15bff5,0xbfe23f71,0xbfffbe49,0xbfc63fa2,
0x3ffdbe96,0xbf84bfdc,0xbf2cbff1,0xbfacbfbe,0x4000,0x4000,0xc000,0x40000000,0xbfb53fb5,0xbfed3f44,0x3fb5bfb5,0x3f443fed,
0xc0000000,0xbfb5bfb5,0x40000000,0xbfb53fb5,0xbfb5bfb5,0x3f44bfed,0x3fb53fb5,0xbfedbf44,0xbfb5bfb5,0xbfb5bfb5,0x3f8e3fd5,0xbfd53f8e,
0x3dc9c000,0x3f5bbfe7,0xbef93ff8,0xbfcebf98,0x3fc6bfa2,0x3fff3e49,0xbfe23f71,0x3f15bff5,0x3ffd3e96,0x3ef93ff8,0xbff1bf2c,0x4000bdc9,
0x40000000,0x40000000,0xbfedbf44,0x3f44bfed,0x3fa23fc6,0x3f153ff5,0xbf15bff5,0x3fff3e49,0xbec83ffb,0xbfd53f8e,0x3f8ebfd5,0x3ec83ffb,
0xbfe23f71,0xbfc6bfa2,0x3fffbe49,0xbfe23f71,0xbfb53fb5,0xbfb53fb5,0x3ffbbec8,0x3ec83ffb,0xbffdbe96,0xbfdcbf84,0x3fbe3fac,0xbfe73f5b,
0xbf71bfe2,0x3f15bff5,0xbe493fff,0xbfa2bfc6,0x3f5bbfe7,0x40003dc9,0xbfdc3f84,0x3f98bfce,0xc000,0xc000,0xbfb53fb5,0xbfb5bfb5,
0x3fd5bf8e,0x3ffbbec8,0xbffbbec8,0x3f8ebfd5,0x3fed3f44,0x3f443fed,0xbf44bfed,0x3fed3f44,0x3ec83ffb,0xbfd53f8e,0x3f8ebfd5,0xbec83ffb,
0x3fb53fb5,0x3fb53fb5,0x3ec8bffb,0x3ffb3ec8,0xbef93ff8,0xbf983fce,0x3ff1bf2c,0xbdc94000,0xbff53f15,0xbfe2bf71,0x3fc63fa2,0xbfff3e49,
0xbfbebfac,0x3f2cbff1,0xbe963ffd,0xbef9bff8,0xc0000000,0xc0000000,0x3f443fed,0xbfed3f44,0xbf71bfe2,0xbe49bfff,0xbfa23fc6,0xbf71bfe2,
0x3f8ebfd5,0x3ffbbec8,0xbffbbec8,0x3fd5bf8e,0x3fff3e49,0x3f153ff5,0xbf15bff5,0x3fa23fc6,0x3fb5bfb5,0x3fb5bfb5,0xbfd5bf8e,0x3f8ebfd5,
0x3ff13f2c,0x3fbe3fac,0x3e96bffd,0x3fdc3f84,0x3e493fff,0xbfa23fc6,0x3ff5bf15,0xbf713fe2,0xbfdc3f84,0xbfcebf98,0x3fac3fbe,0xbfe7bf5b,
0x4000,0xc000,0xc000,0xc0000000,0xbfb53fb5,0x3fedbf44,0x3fb5bfb5,0xbf44bfed,0xc0000000,0x3fb53fb5,0x40000000,0x3fb5bfb5,
0xbfb5bfb5,0xbf443fed,0x3fb53fb5,0x3fed3f44,0xbf44bfed,0x3f443fed,0x3ec83ffb,0x3ffbbec8,0x3f5bbfe7,0xbfbe3fac,0xbf983fce,0x3f843fdc,
0x3ff5bf15,0xbfe2bf71,0xbfff3e49,0xbfa23fc6,0x3fdc3f84,0x3e96bffd,0xbfbebfac,0xbff1bf2c,0x3fb53fb5,0xbfb5bfb5,0xbf44bfed,0xbfed3f44,
0xbe493fff,0x3f71bfe2,0x3f71bfe2,0xbfa2bfc6,0xbfd53f8e,0x3ffb3ec8,0x3ffbbec8,0x3f8ebfd5,0xbff5bf15,0x3e493fff,0x3fc63fa2,0x3ff53f15,
0xbfedbf44,0x3fed3f44,0x3f8e3fd5,0x3fd5bf8e,0xbef9bff8,0xbe963ffd,0xbf2c3ff1,0x3fbe3fac,0x3fa2bfc6,0xbfff3e49,0xbff53f15,0xbf713fe2,
0x40003dc9,0xbf2cbff1,0xbfcebf98,0xbff8bef9,0x40000000,0xc0000000,0xbfb5bfb5,0xbfb53fb5,0x3f8e3fd5,0xbec8bffb,0x3ec8bffb,0xbfd5bf8e,
0xbf443fed,0x3fedbf44,0x3fedbf44,0x3f44bfed,0xbffb3ec8,0x3f8e3fd5,0x3fd53f8e,0x3ffb3ec8,0xbfed3f44,0x3fedbf44,0x3fd53f8e,0x3f8ebfd5,
0xbfcebf98,0x3f843fdc,0xbdc94000,0x3fe73f5b,0x3e49bfff,0xbfc63fa2,0xbfe23f71,0xbf153ff5,0x3fe7bf5b,0xbfbebfac,0xbfdcbf84,0xbffdbe96,
0x3fb5bfb5,0xbfb53fb5,0xbfedbf44,0xbf443fed,0x3ff53f15,0xbfc6bfa2,0xbe49bfff,0xbff5bf15,0x3ec83ffb,0x3f8ebfd5,0x3fd5bf8e,0x3ec8bffb,
0xbfc63fa2,0x3fe23f71,0x3fe23f71,0x3fff3e49,0xbf443fed,0x3f44bfed,0x3ffb3ec8,0x3ec8bffb,0xc0003dc9,0x3ff13f2c,0x3ef93ff8,0x3ffd3e96,
0xbf71bfe2,0xbf153ff5,0xbfc63fa2,0xbe493fff,0x3f98bfce,0xbff8bef9,0xbfe7bf5b,0xc000bdc9,0x3f803f80,0x3f803f80,0x4000,0xc0000000,
0xc0000000,0xbfedbf44,0xc0000000,0x3f44bfed,0xc000,0x3fb5bfb5,0xc000,0x3fb53fb5,0x40000000,0x3f443fed,0x40000000,0xbfed3f44,
0xbf803f80,0xbf803f80,0xbec83ffb,0xbffbbec8,0xc000bdc9,0xbfe7bf5b,0xbff8bef9,0x3f98bfce,0x3e49bfff,0x3fc6bfa2,0x3f15bff5,0x3f713fe2,
0x3ffd3e96,0x3ef93ff8,0x3ff13f2c,0xc0003dc9,0x3f803f80,0x3f803f80,0xbf443fed,0xbfedbf44,0xbfffbe49,0xbfe2bf71,0xbfe2bf71,0x3fc6bfa2,
0x3ec8bffb,0x3fd5bf8e,0x3f8ebfd5,0x3ec83ffb,0x3ff53f15,0x3e493fff,0x3fc63fa2,0xbff5bf15,0xbf803f80,0xbf803f80,0xbf8e3fd5,0xbfd5bf8e,
0xbffdbe96,0xbfdcbf84,0xbfbebfac,0x3fe7bf5b,0x3f15bff5,0x3fe2bf71,0x3fc6bfa2,0xbe493fff,0x3fe73f5b,0xbdc94000,0x3f843fdc,0xbfcebf98,
0x3f803f80,0x3f803f80,0xbfb53fb5,0xbfb5bfb5,0xbffbbec8,0xbfd5bf8e,0xbf8ebfd5,0x3ffbbec8,0x3f44bfed,0x3fedbf44,0x3fedbf44,0xbf443fed,
0x3fd53f8e,0xbec83ffb,0x3ec83ffb,0xbf8ebfd5,0xbf803f80,0xbf803f80,0xbfd53f8e,0xbf8ebfd5,0xbff8bef9,0xbfcebf98,0xbf2cbff1,0x40003dc9,
0x3f71bfe2,0x3ff5bf15,0x3fffbe49,0xbfa23fc6,0x3fbe3fac,0xbf2c3ff1,0xbe963ffd,0xbef9bff8,0x3f803f80,0x3f803f80,0xbfed3f44,0xbf44bfed,
0xbff5bf15,0xbfc6bfa2,0xbe49bfff,0x3ff53f15,0x3f8ebfd5,0x3ffbbec8,0x3ffb3ec8,0xbfd53f8e,0x3fa23fc6,0xbf713fe2,0xbf713fe2,0x3e49bfff,
0xbf803f80,0xbf803f80,0xbffb3ec8,0xbec8bffb,0xbff1bf2c,0xbfbebfac,0x3e96bffd,0x3fdc3f84,0x3fa2bfc6,0x3fffbe49,0x3fe23f71,0xbff53f15,
0x3f843fdc,0xbf983fce,0xbfbe3fac,0x3f5bbfe7,0x4000,0xc000,0x4000,0x40000000,0xc0000000,0x3fed3f44,0xc0000000,0xbf443fed,
0xc000,0xbfb53fb5,0xc000,0xbfb5bfb5,0x40000000,0xbf44bfed,0x40000000,0x3fedbf44,0xbf443fed,0x3f44bfed,0xbf8e3fd5,0x3fd53f8e,
0xbfe7bf5b,0x3fac3fbe,0xbfcebf98,0xbfdc3f84,0x3f71bfe2,0xbff53f15,0x3fa2bfc6,0xbe49bfff,0x3fdc3f84,0x3e96bffd,0x3fbe3fac,0x3ff13f2c,
0xbfb53fb5,0x3fb5bfb5,0xbfed3f44,0x3f443fed,0xbfa2bfc6,0x3f153ff5,0xbf15bff5,0xbfffbe49,0x3fd5bf8e,0xbffbbec8,0x3ffbbec8,0x3f8ebfd5,
0x3f713fe2,0x3fa2bfc6,0x3e493fff,0x3f713fe2,0xbfed3f44,0x3fedbf44,0xbffbbec8,0xbec83ffb,0xbef9bff8,0xbe963ffd,0x3f2cbff1,0xbfbebfac,
0x3fffbe49,0xbfc6bfa2,0x3fe23f71,0x3ff5bf15,0xbdc94000,0x3ff1bf2c,0xbf983fce,0xbef93ff8,0xc0000000,0x40000000,0xbfb5bfb5,0xbfb53fb5,
0x3ec8bffb,0xbf8e3fd5,0x3fd5bf8e,0xbec8bffb,0x3fed3f44,0xbf44bfed,0x3f443fed,0x3fed3f44,0xbf8e3fd5,0x3ffb3ec8,0xbffb3ec8,0xbfd53f8e,
0xbfedbf44,0x3fed3f44,0xbec8bffb,0xbffb3ec8,0x3f98bfce,0xbfdc3f84,0x40003dc9,0x3f5bbfe7,0x3fa23fc6,0x3e49bfff,0xbf153ff5,0x3f713fe2,
0xbfe73f5b,0x3fbe3fac,0xbfdcbf84,0xbffdbe96,0xbfb5bfb5,0x3fb53fb5,0x3f44bfed,0xbfedbf44,0x3fe2bf71,0xbfff3e49,0x3fc63fa2,0x3fe2bf71,
0x3ec83ffb,0x3f8ebfd5,0xbfd53f8e,0xbec83ffb,0xbfffbe49,0x3f153ff5,0xbf15bff5,0xbfa2bfc6,0xbf44bfed,0x3f443fed,0x3fd5bf8e,0xbf8ebfd5,
0x4000bdc9,0xbff1bf2c,0x3ef93ff8,0x3ffd3e96,0xbf153ff5,0x3fe2bf71,0xbfffbe49,0xbfc63fa2,0xbfcebf98,0xbef93ff8,0x3f5bbfe7,0x3dc9c000,
0x4000,0x4000,0x4000,0xc0000000,0xc0000000,0xbfedbf44,0xc0000000,0x3f44bfed,0xc000,0x3fb5bfb5,0xc000,0x3fb53fb5,
0x40000000,0x3f443fed,0x40000000,0xbfed3f44,0xbfb53fb5,0xbfb53fb5,0xbfd53f8e,0xbf8ebfd5,0xbfacbfbe,0xbf2cbff1,0xbf84bfdc,0x3ffdbe96,
0x3fc6bfa2,0x3fff3e49,0x3fe2bf71,0xbf153ff5,0x3f983fce,0xbf843fdc,0x3f5b3fe7,0xbfbebfac,0xc0000000,0xc0000000,0xbfedbf44,0x3f44bfed,
0x3e49bfff,0x3f71bfe2,0x3f71bfe2,0x3fa23fc6,0x3ffb3ec8,0x3f8e3fd5,0x3fd53f8e,0xbffb3ec8,0xbf153ff5,0xbfff3e49,0xbfa23fc6,0x3f15bff5,
0xbfb5bfb5,0xbfb5bfb5,0xbec8bffb,0x3ffbbec8,0x3fcebf98,0x3ff8bef9,0x4000bdc9,0xbf2c3ff1,0x3f713fe2,0xbf153ff5,0xbe493fff,0xbfa2bfc6,
0xbff13f2c,0xbfacbfbe,0xbff8bef9,0x3ffdbe96,0xc000,0xc000,0x3fb5bfb5,0x3fb53fb5,0x3ffb3ec8,0x3fd53f8e,0x3f8e3fd5,0xbffb3ec8,
0xbf443fed,0xbfed3f44,0xbfed3f44,0x3f44bfed,0xbfd5bf8e,0x3ec8bffb,0xbec8bffb,0x3f8e3fd5,0x3fb5bfb5,0x3fb5bfb5,0x3ffb3ec8,0xbec83ffb,
0x3f843fdc,0x3e963ffd,0xbf5b3fe7,0xbfacbfbe,0xbff53f15,0xbfe2bf71,0xbfc6bfa2,0x3fffbe49,0xbdc9c000,0x3fe7bf5b,0x3fcebf98,0xbf843fdc,
0x40000000,0x40000000,0x3f443fed,0xbfed3f44,0xbf153ff5,0xbfa23fc6,0xbfff3e49,0x3f15bff5,0xbfd5bf8e,0xbec8bffb,0x3ec8bffb,0x3f8e3fd5,
0x3fc6bfa2,0x3fe23f71,0x3fe23f71,0xbfffbe49,0x3fb53fb5,0x3fb53fb5,0xbf8e3fd5,0xbfd5bf8e,0xbfe73f5b,0xc0003dc9,0xbf98bfce,0x3ff8bef9,
0xbe49bfff,0x3fa2bfc6,0x3ff5bf15,0xbf713fe2,0x3ff83ef9,0x3e963ffd,0xbdc94000,0xbf2cbff1,0x4000,0xc000,0x4000,0x40000000,
0xc0000000,0x3fed3f44,0xc0000000,0xbf443fed,0xc000,0xbfb53fb5,0xc000,0xbfb5bfb5,0x40000000,0xbf44bfed,0x40000000,0x3fedbf44,
0xbfed3f44,0x3fedbf44,0xbffb3ec8,0x3ec83ffb,0xbf2cbff1,0xbdc94000,0xbe96bffd,0xbff8bef9,0x3ff5bf15,0xbfe2bf71,0x3fffbe49,0x3fa2bfc6,
0x3ef93ff8,0x3fcebf98,0x3dc94000,0x3f5b3fe7,0xbfb5bfb5,0x3fb53fb5,0xbf44bfed,0xbfed3f44,0x3fc6bfa2,0xbff53f15,0x3ff5bf15,0x3e49bfff,
0x3f8e3fd5,0x3ec8bffb,0x3ec83ffb,0x3fd53f8e,0xbfe23f71,0x3fc63fa2,0xbfff3e49,0xbfe23f71,0x3f44bfed,0xbf443fed,0x3fd5bf8e,0xbf8ebfd5,
0x3fdc3f84,0xbf98bfce,0x3f5b3fe7,0x4000bdc9,0xbfa23fc6,0x3fffbe49,0xbff53f15,0xbf713fe2,0xbfacbfbe,0xbf5b3fe7,0xbe96bffd,0xbf84bfdc,
0x40000000,0xc0000000,0x3fb53fb5,0x3fb5bfb5,0xbec83ffb,0x3f8ebfd5,0xbfd53f8e,0x3ec83ffb,0xbfedbf44,0x3f443fed,0xbf44bfed,0xbfedbf44,
0x3f8ebfd5,0xbffbbec8,0x3ffbbec8,0x3fd5bf8e,0x3f443fed,0xbf44bfed,0xbf8e3fd5,0x3fd53f8e,0xbffd3e96,0x3ff83ef9,0xbfacbfbe,0xbff13f2c,
0x3e49bfff,0xbfc63fa2,0x3fe2bf71,0x3f15bff5,0x3ff13f2c,0xbdc9c000,0x3ef93ff8,0x3f983fce,0xbfb53fb5,0x3fb5bfb5,0xbfedbf44,0xbf443fed,
0xbf71bfe2,0x3e493fff,0x3fa2bfc6,0xbf71bfe2,0x3ffbbec8,0xbfd5bf8e,0x3f8e3fd5,0x3ffb3ec8,0xbe493fff,0x3ff5bf15,0xbff53f15,0xbfc63fa2,
0xbfedbf44,0x3fed3f44,0x3ec8bffb,0xbffbbec8,0x3facbfbe,0xbfe73f5b,0x3fdc3f84,0x3fcebf98,0x3f713fe2,0x3f15bff5,0xbfc63fa2,0xbe493fff,
0xbffd3e96,0x3f843fdc,0xbf2cbff1,0xbfacbfbe,0x4000,0x4000,0x4000,0xc0000000,0xc0000000,0xbfedbf44,0xc0000000,0x3f44bfed,
0xc000,0x3fb5bfb5,0xc000,0x3fb53fb5,0x40000000,0x3f443fed,0x40000000,0xbfed3f44,0xc0000000,0xc0000000,0xbffbbec8,0x3ec8bffb,
0x3dc9c000,0x3f5bbfe7,0x3ef9bff8,0x3fce3f98,0x3fff3e49,0x3fa23fc6,0x3ff53f15,0xbfe23f71,0xbe963ffd,0xbff83ef9,0xbf2c3ff1,0xbdc9c000,
0xc000,0xc000,0x3f44bfed,0x3fed3f44,0x3fff3e49,0x3fe23f71,0x3fe23f71,0xbfc63fa2,0xbec83ffb,0xbfd53f8e,0xbf8e3fd5,0xbec8bffb,
0xbff5bf15,0xbe49bfff,0xbfc6bfa2,0x3ff53f15,0x40000000,0x40000000,0x3fd53f8e,0xbf8e3fd5,0xbe963ffd,0xbf843fdc,0xbfac3fbe,0xbf5bbfe7,
0xbff5bf15,0xbf71bfe2,0xbfa2bfc6,0x3fff3e49,0x3f5bbfe7,0x40003dc9,0x3fdcbf84,0xbf983fce,0x4000,0x4000,0xbfb53fb5,0xbfb5bfb5,
0xbffbbec8,0xbfd5bf8e,0xbf8ebfd5,0x3ffbbec8,0x3f44bfed,0x3fedbf44,0x3fedbf44,0xbf443fed,0x3fd53f8e,0xbec83ffb,0x3ec83ffb,0xbf8ebfd5,
0xc0000000,0xc0000000,0xbf8ebfd5,0x3fd5bf8e,0x3ef9bff8,0x3f98bfce,0x3ff1bf2c,0xbdc94000,0x3fe23f71,0x3f153ff5,0x3e493fff,0xbfc6bfa2,
0xbfac3fbe,0xbff1bf2c,0xbffdbe96,0x3ff8bef9,0xc000,0xc000,0x3fedbf44,0x3f443fed,0x3ff53f15,0x3fc63fa2,0x3e493fff,0xbff5bf15,
0xbf8e3fd5,0xbffb3ec8,0xbffbbec8,0x3fd5bf8e,0xbfa2bfc6,0x3f71bfe2,0x3f71bfe2,0xbe493fff,0x40000000,0x40000000,0x3ec83ffb,0xbffb3ec8,
0xbf2c3ff1,0xbfac3fbe,0xbffdbe96,0x3f84bfdc,0xbfc6bfa2,0xbe49bfff,0x3f71bfe2,0x3f153ff5,0x3fdcbf84,0x3fce3f98,0x3fac3fbe,0xbfe7bf5b,
0x4000,0xc000,0x4000,0x40000000,0xc0000000,0x3fed3f44,0xc0000000,0xbf443fed,0xc000,0xbfb53fb5,0xc000,0xbfb5bfb5,
0x40000000,0xbf44bfed,0x40000000,0x3fedbf44,0xbfedbf44,0x3fed3f44,0xbfd5bf8e,0xbf8e3fd5,0x3f5bbfe7,0xbfbe3fac,0x3f98bfce,0xbf84bfdc,
0x3fe23f71,0xbf15bff5,0x3fc63fa2,0x3fffbe49,0xbf843fdc,0x3ffd3e96,0xbfac3fbe,0xbf2c3ff1,0x3fb5bfb5,0xbfb53fb5,0x3fedbf44,0xbf44bfed,
0x3fa23fc6,0xbf15bff5,0x3f153ff5,0x3fff3e49,0xbfd53f8e,0x3ffb3ec8,0xbffb3ec8,0xbf8e3fd5,0xbf71bfe2,0xbfa23fc6,0xbe49bfff,0xbf71bfe2,
0x3f443fed,0xbf44bfed,0xbec83ffb,0x3ffb3ec8,0xbff83ef9,0x3ffd3e96,0xbff1bf2c,0xbfac3fbe,0xbe49bfff,0xbfa23fc6,0x3f71bfe2,0xbf15bff5,
0x40003dc9,0xbf2cbff1,0x3fce3f98,0x3ff83ef9,0xc0000000,0x40000000,0xbfb5bfb5,0xbfb53fb5,0x3ec8bffb,0xbf8e3fd5,0x3fd5bf8e,0xbec8bffb,
0x3fed3f44,0xbf44bfed,0x3f443fed,0x3fed3f44,0xbf8e3fd5,0x3ffb3ec8,0xbffb3ec8,0xbfd53f8e,0x3f44bfed,0xbf443fed,0x3ffbbec8,0xbec8bffb,
0x3fce3f98,0xbf84bfdc,0xbdc94000,0x3fe73f5b,0xbfc63fa2,0x3fff3e49,0xbff5bf15,0xbfe23f71,0xbf5bbfe7,0xbfac3fbe,0x3f84bfdc,0x3e96bffd,
0x3fb53fb5,0xbfb5bfb5,0xbf443fed,0x3fed3f44,0xbfe23f71,0x3fffbe49,0xbfc6bfa2,0xbfe23f71,0xbec8bffb,0xbf8e3fd5,0x3fd5bf8e,0x3ec8bffb,
0x3fff3e49,0xbf15bff5,0x3f153ff5,0x3fa23fc6,0xbfed3f44,0x3fedbf44,0xbf8ebfd5,0xbfd53f8e,0xbdc9c000,0xbf2c3ff1,0x3ff8bef9,0x3e96bffd,
0x3ff53f15,0xbf71bfe2,0xbe493fff,0x3fa23fc6,0xbf983fce,0x3ff83ef9,0xbfe7bf5b,0xc000bdc9,0x4000,0x4000,0x4000,0xc0000000,
0xc0000000,0xbfedbf44,0xc0000000,0x3f44bfed,0xc000,0x3fb5bfb5,0xc000,0x3fb53fb5,0x40000000,0x3f443fed,0x40000000,0xbfed3f44,
0xbfb5bfb5,0xbfb5bfb5,0xbf8ebfd5,0x3fd5bf8e,0x3fbebfac,0x3ff1bf2c,0x3fdcbf84,0x3e963ffd,0x3fa23fc6,0xbe493fff,0x3f713fe2,0xbff5bf15,
0xbfce3f98,0xbfdcbf84,0xbfe73f5b,0x3facbfbe,0x40000000,0x40000000,0x3fed3f44,0xbf443fed,0xbe493fff,0xbf713fe2,0xbf713fe2,0xbfa2bfc6,
0xbffbbec8,0xbf8ebfd5,0xbfd5bf8e,0x3ffbbec8,0x3f15bff5,0x3fffbe49,0x3fa2bfc6,0xbf153ff5,0xbfb53fb5,0xbfb53fb5,0xbffb3ec8,0xbec8bffb,
0xbf98bfce,0xbef9bff8,0xbdc9c000,0x3ff13f2c,0x3fe2bf71,0x3ff53f15,0x3fff3e49,0xbfc63fa2,0x3f2c3ff1,0xbfbe3fac,0xbef93ff8,0xbe96bffd,
0xc000,0xc000,0x3fb5bfb5,0x3fb53fb5,0x3ffb3ec8,0x3fd53f8e,0x3f8e3fd5,0xbffb3ec8,0xbf443fed,0xbfed3f44,0xbfed3f44,0x3f44bfed,
0xbfd5bf8e,0x3ec8bffb,0xbec8bffb,0x3f8e3fd5,0x3fb53fb5,0x3fb53fb5,0xbec83ffb,0xbffbbec8,0xbfdc3f84,0xbffd3e96,0xbfe7bf5b,0x3fbebfac,
0xbf15bff5,0x3f71bfe2,0x3fa2bfc6,0x3e493fff,0x4000bdc9,0x3f5b3fe7,0x3f983fce,0xbfdcbf84,0xc0000000,0xc0000000,0xbf44bfed,0x3fedbf44,
0x3f15bff5,0x3fa2bfc6,0x3fffbe49,0xbf153ff5,0x3fd53f8e,0x3ec83ffb,0xbec83ffb,0xbf8ebfd5,0xbfc63fa2,0xbfe2bf71,0xbfe2bf71,0x3fff3e49,
0x3fb5bfb5,0x3fb5bfb5,0x3fd53f8e,0xbf8e3fd5,0x3f5b3fe7,0x3dc94000,0xbfce3f98,0xbef9bff8,0xbfff3e49,0xbfc6bfa2,0xbf15bff5,0x3fe23f71,
0x3ef9bff8,0x3ffdbe96,0x40003dc9,0xbff13f2c,0x4000,0xc000,0x4000,0x40000000,0xc0000000,0x3fed3f44,0xc0000000,0xbf443fed,
0xc000,0xbfb53fb5,0xc000,0xbfb5bfb5,0x40000000,0xbf44bfed,0x40000000,0x3fedbf44,0xbf44bfed,0x3f443fed,0xbec8bffb,0xbffb3ec8,
0x3ff1bf2c,0xc000bdc9,0x3ffdbe96,0x3ef9bff8,0x3f153ff5,0x3f71bfe2,0x3e493fff,0x3fc63fa2,0xbff83ef9,0x3f983fce,0xc0003dc9,0xbfe73f5b,
0x3fb53fb5,0xbfb5bfb5,0x3f443fed,0x3fedbf44,0xbfc63fa2,0x3ff5bf15,0xbff53f15,0xbe493fff,0xbf8ebfd5,0xbec83ffb,0xbec8bffb,0xbfd5bf8e,
0x3fe2bf71,0xbfc6bfa2,0x3fffbe49,0x3fe2bf71,0xbfedbf44,0x3fed3f44,0xbf8ebfd5,0xbfd53f8e,0x3f84bfdc,0xbfce3f98,0x3fe7bf5b,0xbdc9c000,
0x3fc63fa2,0xbe49bfff,0x3f153ff5,0x3fe23f71,0xbfbe3fac,0x3fe73f5b,0xbffd3e96,0xbfdc3f84,0x40000000,0xc0000000,0x3fb53fb5,0x3fb5bfb5,
0xbec83ffb,0x3f8ebfd5,0xbfd53f8e,0x3ec83ffb,0xbfedbf44,0x3f443fed,0xbf44bfed,0xbfedbf44,0x3f8ebfd5,0xbffbbec8,0x3ffbbec8,0x3fd5bf8e,
0xbfed3f44,0x3fedbf44,0xbfd5bf8e,0xbf8e3fd5,0xbe96bffd,0xbef93ff8,0x3fbebfac,0xbf2cbff1,0x3fff3e49,0xbfa2bfc6,0x3f713fe2,0x3ff53f15,
0xbf2c3ff1,0x4000bdc9,0xbff83ef9,0xbfce3f98,0x3fb5bfb5,0xbfb53fb5,0x3fed3f44,0x3f44bfed,0x3f713fe2,0xbe49bfff,0xbfa23fc6,0x3f713fe2,
0xbffb3ec8,0x3fd53f8e,0xbf8ebfd5,0xbffbbec8,0x3e49bfff,0xbff53f15,0x3ff5bf15,0x3fc6bfa2,0xbf443fed,0x3f44bfed,0xbffbbec8,0xbec83ffb,
0xbfbebfac,0x3f5b3fe7,0x3f84bfdc,0xbf98bfce,0x3fe2bf71,0xbff5bf15,0x3fa23fc6,0x3fff3e49,0x3e963ffd,0x3fdcbf84,0xbff13f2c,0xbfbe3fac,
0x3f803f80,0x3f803f80,0xc000,0x40000000,0xbfb5bfb5,0xbf44bfed,0x3fb53fb5,0xbfed3f44,0x40000000,0x3fb53fb5,0xc0000000,0x3fb5bfb5,
0xbfb53fb5,0xbfedbf44,0x3fb5bfb5,0xbf443fed,0xbf803f80,0xbf803f80,0x3ec8bffb,0x3ffb3ec8,0xbfacbfbe,0xbf2cbff1,0x3f843fdc,0xbffd3e96,
0x3fff3e49,0x3fa23fc6,0xbff5bf15,0x3fe2bf71,0xbfce3f98,0xbfdcbf84,0x3fe7bf5b,0xbfac3fbe,0x3f803f80,0x3f803f80,0x3f44bfed,0x3fed3f44,
0xbfa2bfc6,0xbf15bff5,0x3f153ff5,0xbfffbe49,0x3ffb3ec8,0x3f8e3fd5,0xbfd5bf8e,0x3ffbbec8,0xbfe23f71,0xbfc6bfa2,0x3fffbe49,0xbfe23f71,
0xbf803f80,0xbf803f80,0x3f8ebfd5,0x3fd53f8e,0xbf98bfce,0xbef9bff8,0x3dc94000,0xbff1bf2c,0x3ff53f15,0x3f713fe2,0xbfa2bfc6,0x3fff3e49,
0xbff13f2c,0xbfacbfbe,0x3ff83ef9,0xbffd3e96,0x3f803f80,0x3f803f80,0x3fb5bfb5,0x3fb53fb5,0xbf8ebfd5,0xbec8bffb,0xbec83ffb,0xbfd5bf8e,
0x3fed3f44,0x3f443fed,0xbf44bfed,0x3fed3f44,0xbffb3ec8,0xbf8ebfd5,0x3fd53f8e,0xbffbbec8,0xbf803f80,0xbf803f80,0x3fd5bf8e,0x3f8e3fd5,
0xbf84bfdc,0xbe96bffd,0xbf5b3fe7,0xbfacbfbe,0x3fe23f71,0x3f153ff5,0xbe49bfff,0x3fc63fa2,0xc0003dc9,0xbf5bbfe7,0x3f983fce,0xbfdcbf84,
0x3f803f80,0x3f803f80,0x3fedbf44,0x3f443fed,0xbf71bfe2,0xbe49bfff,0xbfa23fc6,0xbf71bfe2,0x3fd53f8e,0x3ec83ffb,0x3ec8bffb,0x3f8e3fd5,
0xbfffbe49,0xbf15bff5,0x3f153ff5,0xbfa2bfc6,0xbf803f80,0xbf803f80,0x3ffbbec8,0x3ec83ffb,0xbf5bbfe7,0xbdc9c000,0xbfce3f98,0xbef9bff8,
0x3fc63fa2,0x3e493fff,0x3f71bfe2,0x3f153ff5,0xbff8bef9,0xbe96bffd,0xbdc94000,0xbf2cbff1,0x4000,0xc000,0xc000,0xc0000000,
0xbfb5bfb5,0x3f443fed,0x3fb53fb5,0x3fedbf44,0x40000000,0xbfb5bfb5,0xc0000000,0xbfb53fb5,0xbfb53fb5,0x3fed3f44,0x3fb5bfb5,0x3f44bfed,
0xbf443fed,0x3f44bfed,0x3f8ebfd5,0xbfd5bf8e,0xbf2cbff1,0xbdc94000,0x3e963ffd,0x3ff83ef9,0x3fe23f71,0xbf15bff5,0xbfc6bfa2,0xbfff3e49,
0xbff83ef9,0x3f983fce,0x4000bdc9,0x3fe7bf5b,0xbfb53fb5,0x3fb5bfb5,0x3fedbf44,0xbf44bfed,0x3e49bfff,0xbf713fe2,0xbf713fe2,0x3fa23fc6,
0x3f8e3fd5,0x3ec8bffb,0xbec8bffb,0xbfd5bf8e,0xbff5bf15,0x3e493fff,0x3fc63fa2,0x3ff53f15,0xbfed3f44,0x3fedbf44,0x3ffb3ec8,0x3ec8bffb,
0x3f84bfdc,0xbfce3f98,0xbfe73f5b,0x3dc94000,0x3e493fff,0x3fa2bfc6,0x3f71bfe2,0xbf15bff5,0xbfacbfbe,0xbf5b3fe7,0x3e963ffd,0x3f843fdc,
0xc0000000,0x40000000,0x3fb53fb5,0x3fb5bfb5,0x3fd5bf8e,0xbffb3ec8,0xbffbbec8,0xbf8e3fd5,0xbf443fed,0x3fedbf44,0x3fedbf44,0x3f44bfed,
0xbec8bffb,0xbfd53f8e,0xbf8e3fd5,0xbec83ffb,0xbfedbf44,0x3fed3f44,0x3ec83ffb,0x3ffbbec8,0x3ffdbe96,0xbff8bef9,0xbfacbfbe,0xbff13f2c,
0xbfc63fa2,0x3fff3e49,0x3ff53f15,0x3fe2bf71,0x3f2cbff1,0xc0003dc9,0xbff83ef9,0xbfce3f98,0xbfb5bfb5,0x3fb53fb5,0xbf443fed,0x3fed3f44,
0x3ff53f15,0xbfc6bfa2,0xbe49bfff,0xbff5bf15,0xbffb3ec8,0x3fd53f8e,0x3f8e3fd5,0x3ffb3ec8,0x3fc6bfa2,0xbfe2bf71,0xbfe2bf71,0xbfffbe49,
0xbf44bfed,0x3f443fed,0xbfd53f8e,0x3f8e3fd5,0x3fbe3fac,0xbf5bbfe7,0x3f84bfdc,0xbf98bfce,0xbff5bf15,0x3f713fe2,0xbe493fff,0x3fa23fc6,
0x3ffdbe96,0xbf84bfdc,0xbf2cbff1,0xbfacbfbe,0x4000,0x4000,0xc000,0x40000000,0xbfb5bfb5,0xbf44bfed,0x3fb53fb5,0xbfed3f44,
0x40000000,0x3fb53fb5,0xc0000000,0x3fb5bfb5,0xbfb53fb5,0xbfedbf44,0x3fb5bfb5,0xbf443fed,0xbfb53fb5,0xbfb53fb5,0x3fd5bf8e,0x3f8e3fd5,
0x3dc9c000,0x3f5bbfe7,0xbef93ff8,0xbfcebf98,0x3fa23fc6,0xbe493fff,0xbf71bfe2,0x3ff53f15,0xbffdbe96,0xbef9bff8,0x3ff13f2c,0xc0003dc9,
0xc0000000,0xc0000000,0x3fed3f44,0xbf443fed,0x3fc6bfa2,0x3ff5bf15,0xbff53f15,0x3e49bfff,0xbec83ffb,0xbfd53f8e,0x3f8ebfd5,0x3ec83ffb,
0xbf71bfe2,0x3fa2bfc6,0x3e493fff,0xbf71bfe2,0xbfb5bfb5,0xbfb5bfb5,0x3ec83ffb,0xbffb3ec8,0x3ffd3e96,0x3fdc3f84,0xbfbebfac,0x3fe7bf5b,
0xbfe23f71,0xbff5bf15,0x3fff3e49,0xbfc63fa2,0x3f5bbfe7,0x40003dc9,0xbfdc3f84,0x3f98bfce,0xc000,0xc000,0xbfb53fb5,0xbfb5bfb5,
0x3f8e3fd5,0x3ec83ffb,0x3ec8bffb,0x3fd53f8e,0xbfedbf44,0xbf44bfed,0x3f443fed,0xbfedbf44,0x3ffbbec8,0x3f8e3fd5,0xbfd5bf8e,0x3ffb3ec8,
0x3fb5bfb5,0x3fb5bfb5,0xbffbbec8,0x3ec8bffb,0xbef93ff8,0xbf983fce,0x3ff1bf2c,0xbdc94000,0xbf15bff5,0x3f71bfe2,0xbfa23fc6,0xbe49bfff,
0x3fbe3fac,0xbf2c3ff1,0x3e96bffd,0x3ef93ff8,0x40000000,0x40000000,0xbf44bfed,0x3fedbf44,0xbfe23f71,0xbfff3e49,0x3fc63fa2,0xbfe23f71,
0x3f8ebfd5,0x3ffbbec8,0xbffbbec8,0x3fd5bf8e,0xbe493fff,0xbff53f15,0x3ff5bf15,0xbfc63fa2,0x3fb53fb5,0x3fb53fb5,0x3f8ebfd5,0x3fd53f8e,
0xbff1bf2c,0xbfbebfac,0xbe963ffd,0xbfdcbf84,0x3fffbe49,0x3fc63fa2,0xbf15bff5,0x3fe23f71,0xbfdc3f84,0xbfcebf98,0x3fac3fbe,0xbfe7bf5b,
0x4000,0xc000,0xc000,0xc0000000,0xbfb5bfb5,0x3f443fed,0x3fb53fb5,0x3fedbf44,0x40000000,0xbfb5bfb5,0xc0000000,0xbfb53fb5,
0xbfb53fb5,0x3fed3f44,0x3fb5bfb5,0x3f44bfed,0xbfed3f44,0x3fedbf44,0x3ffbbec8,0xbec8bffb,0x3f5bbfe7,0xbfbe3fac,0xbf983fce,0x3f843fdc,
0x3f153ff5,0x3f71bfe2,0xbe49bfff,0xbfc6bfa2,0xbfdcbf84,0xbe963ffd,0x3fbe3fac,0x3ff13f2c,0xbfb5bfb5,0x3fb53fb5,0x3f443fed,0x3fedbf44,
0x3fff3e49,0xbfe2bf71,0xbfe2bf71,0xbfc63fa2,0xbfd53f8e,0x3ffb3ec8,0x3ffbbec8,0x3f8ebfd5,0x3f15bff5,0xbfff3e49,0xbfa23fc6,0xbf153ff5,
0x3f44bfed,0xbf443fed,0xbfd53f8e,0x3f8e3fd5,0x3ef93ff8,0x3e96bffd,0x3f2cbff1,0xbfbebfac,0xbfc6bfa2,0x3e493fff,0x3f153ff5,0x3fe23f71,
0x40003dc9,0xbf2cbff1,0xbfcebf98,0xbff8bef9,0x40000000,0xc0000000,0xbfb5bfb5,0xbfb53fb5,0xbfd53f8e,0x3ffbbec8,0x3ffb3ec8,0x3f8ebfd5,
0x3f44bfed,0xbfed3f44,0xbfed3f44,0xbf443fed,0x3ec83ffb,0x3fd5bf8e,0x3f8ebfd5,0x3ec8bffb,0x3f443fed,0xbf44bfed,0x3f8ebfd5,0xbfd5bf8e,
0xbfcebf98,0x3f843fdc,0xbdc94000,0x3fe73f5b,0x3fff3e49,0xbfa2bfc6,0xbf71bfe2,0xbff5bf15,0xbfe73f5b,0x3fbe3fac,0x3fdc3f84,0x3ffd3e96,
0xbfb53fb5,0x3fb5bfb5,0x3fed3f44,0x3f44bfed,0x3f15bff5,0xbfa23fc6,0xbfff3e49,0xbf153ff5,0x3ec83ffb,0x3f8ebfd5,0x3fd5bf8e,0x3ec8bffb,
0xbfa2bfc6,0xbf713fe2,0xbf713fe2,0xbe493fff,0xbfedbf44,0x3fed3f44,0xbec83ffb,0x3ffb3ec8,0x4000bdc9,0xbff1bf2c,0xbef9bff8,0xbffdbe96,
0xbfe23f71,0x3ff53f15,0x3fa23fc6,0x3fff3e49,0x3f98bfce,0xbff8bef9,0xbfe7bf5b,0xc000bdc9,0x4000,0x4000,0xc000,0x40000000,
0xbfb5bfb5,0xbf44bfed,0x3fb53fb5,0xbfed3f44,0x40000000,0x3fb53fb5,0xc0000000,0x3fb5bfb5,0xbfb53fb5,0xbfedbf44,0x3fb5bfb5,0xbf443fed,
0xc0000000,0xc0000000,0x3ffb3ec8,0xbec83ffb,0x3fbebfac,0x3ff1bf2c,0xbfdc3f84,0xbe96bffd,0xbe493fff,0xbfc63fa2,0x3f15bff5,0x3f713fe2,
0xbf98bfce,0x3f84bfdc,0x3f5b3fe7,0xbfbebfac,0xc000,0xc000,0xbf443fed,0xbfedbf44,0x3fa23fc6,0x3f153ff5,0xbf15bff5,0x3fff3e49,
0xbffbbec8,0xbf8ebfd5,0x3fd53f8e,0xbffb3ec8,0x3fe2bf71,0x3fc63fa2,0xbfff3e49,0x3fe2bf71,0x40000000,0x40000000,0xbfd5bf8e,0x3f8ebfd5,
0xbfce3f98,0xbff83ef9,0x4000bdc9,0xbf2c3ff1,0x3f15bff5,0x3fe2bf71,0xbfc63fa2,0x3e49bfff,0x3f2c3ff1,0xbfbe3fac,0x3ef9bff8,0x3e963ffd,
0x4000,0x4000,0x3fb5bfb5,0x3fb53fb5,0xbf8ebfd5,0xbec8bffb,0xbec83ffb,0xbfd5bf8e,0x3fed3f44,0x3f443fed,0xbf44bfed,0x3fed3f44,
0xbffb3ec8,0xbf8ebfd5,0x3fd53f8e,0xbffbbec8,0xc0000000,0xc0000000,0x3f8e3fd5,0xbfd53f8e,0x3fdcbf84,0x3ffdbe96,0xbfe7bf5b,0x3fbebfac,
0xbf713fe2,0xbff53f15,0x3fffbe49,0xbfa23fc6,0xbdc9c000,0x3fe7bf5b,0xbfce3f98,0x3f84bfdc,0xc000,0xc000,0xbfed3f44,0xbf44bfed,
0x3f713fe2,0x3e493fff,0x3fa2bfc6,0x3f713fe2,0xbfd5bf8e,0xbec8bffb,0xbec83ffb,0xbf8ebfd5,0x3fff3e49,0x3f153ff5,0xbf15bff5,0x3fa23fc6,
0x40000000,0x40000000,0xbec8bffb,0x3ffbbec8,0xbfe73f5b,0xc0003dc9,0x3f983fce,0xbff83ef9,0x3fa2bfc6,0x3fffbe49,0xbfe2bf71,0x3ff5bf15,
0xbef93ff8,0xbffd3e96,0x40003dc9,0xbff13f2c,0x4000,0xc000,0xc000,0xc0000000,0xbfb5bfb5,0x3f443fed,0x3fb53fb5,0x3fedbf44,
0x40000000,0xbfb5bfb5,0xc0000000,0xbfb53fb5,0xbfb53fb5,0x3fed3f44,0x3fb5bfb5,0x3f44bfed,0xbfedbf44,0x3fed3f44,0x3fd53f8e,0x3f8ebfd5,
0x3ff1bf2c,0xc000bdc9,0xbffd3e96,0xbef93ff8,0xbf713fe2,0x3ff5bf15,0x3fa2bfc6,0xbe49bfff,0xbef9bff8,0xbfce3f98,0x3dc94000,0x3f5b3fe7,
0x3fb5bfb5,0xbfb53fb5,0xbfed3f44,0x3f443fed,0xbe493fff,0x3f71bfe2,0x3f71bfe2,0xbfa2bfc6,0xbf8ebfd5,0xbec83ffb,0x3ec83ffb,0x3fd53f8e,
0x3ff53f15,0xbe49bfff,0xbfc6bfa2,0xbff5bf15,0x3f443fed,0xbf44bfed,0x3ec8bffb,0xbffbbec8,0xbfdcbf84,0x3f983fce,0x3f5b3fe7,0x4000bdc9,
0x3fffbe49,0xbfc6bfa2,0xbfe2bf71,0xbff53f15,0xbfbe3fac,0x3fe73f5b,0x3ffdbe96,0x3fdcbf84,0xc0000000,0x40000000,0x3fb53fb5,0x3fb5bfb5,
0x3fd5bf8e,0xbffb3ec8,0xbffbbec8,0xbf8e3fd5,0xbf443fed,0x3fedbf44,0x3fedbf44,0x3f44bfed,0xbec8bffb,0xbfd53f8e,0xbf8e3fd5,0xbec83ffb,
0x3f44bfed,0xbf443fed,0xbffb3ec8,0x3ec83ffb,0x3e963ffd,0x3ef9bff8,0x3fbebfac,0xbf2cbff1,0xbfa2bfc6,0xbe493fff,0xbf153ff5,0x3f713fe2,
0x3ff13f2c,0xbdc9c000,0xbef9bff8,0xbf98bfce,0x3fb53fb5,0xbfb5bfb5,0x3f44bfed,0xbfedbf44,0xbff5bf15,0x3fc63fa2,0x3e493fff,0x3ff53f15,
0x3ffbbec8,0xbfd5bf8e,0xbf8ebfd5,0xbffbbec8,0xbfc63fa2,0x3fe23f71,0x3fe23f71,0x3fff3e49,0xbfed3f44,0x3fedbf44,0x3f8e3fd5,0x3fd5bf8e,
0x3facbfbe,0xbfe73f5b,0xbfdcbf84,0xbfce3f98,0xbf153ff5,0x3fe2bf71,0x3fff3e49,0x3fc6bfa2,0xbe96bffd,0xbfdc3f84,0xbff13f2c,0xbfbe3fac,
0x4000,0x4000,0xc000,0x40000000,0xbfb5bfb5,0xbf44bfed,0x3fb53fb5,0xbfed3f44,0x40000000,0x3fb53fb5,0xc0000000,0x3fb5bfb5,
0xbfb53fb5,0xbfedbf44,0x3fb5bfb5,0xbf443fed,0xbfb5bfb5,0xbfb5bfb5,0x3f8e3fd5,0xbfd53f8e,0x40003dc9,0x3fe73f5b,0xbff8bef9,0x3f98bfce,
0xbfc63fa2,0xbfffbe49,0x3fe2bf71,0xbf153ff5,0x3e96bffd,0x3ff8bef9,0xbf2c3ff1,0xbdc9c000,0x40000000,0x40000000,0xbfedbf44,0x3f44bfed,
0xbfc63fa2,0xbff53f15,0x3ff5bf15,0xbe493fff,0x3ec8bffb,0x3fd5bf8e,0xbf8e3fd5,0xbec8bffb,0x3f713fe2,0xbfa23fc6,0xbe49bfff,0x3f713fe2,
0xbfb53fb5,0xbfb53fb5,0x3ffbbec8,0x3ec83ffb,0x3e96bffd,0x3f84bfdc,0xbfac3fbe,0xbf5bbfe7,0x3f713fe2,0xbf153ff5,0x3e49bfff,0x3fa23fc6,
0xbfe7bf5b,0x3dc9c000,0x3f843fdc,0xbfcebf98,0xc000,0xc000,0xbfb53fb5,0xbfb5bfb5,0x3f8e3fd5,0x3ec83ffb,0x3ec8bffb,0x3fd53f8e,
0xbfedbf44,0xbf44bfed,0x3f443fed,0xbfedbf44,0x3ffbbec8,0x3f8e3fd5,0xbfd5bf8e,0x3ffb3ec8,0x3fb53fb5,0x3fb53fb5,0x3ec8bffb,0x3ffb3ec8,
0xbff8bef9,0xbfcebf98,0x3f2c3ff1,0xc000bdc9,0x3ff5bf15,0x3fe23f71,0xbfc6bfa2,0x3fffbe49,0xbfac3fbe,0xbff1bf2c,0x3ffd3e96,0xbff83ef9,
0xc0000000,0xc0000000,0x3f443fed,0xbfed3f44,0x3fe2bf71,0x3fffbe49,0xbfc6bfa2,0x3fe2bf71,0xbf8e3fd5,0xbffb3ec8,0x3ffb3ec8,0xbfd53f8e,
0x3e49bfff,0x3ff5bf15,0xbff53f15,0x3fc6bfa2,0x3fb5bfb5,0x3fb5bfb5,0xbfd5bf8e,0x3f8ebfd5,0xbf2c3ff1,0xbfac3fbe,0x3ffd3e96,0xbf843fdc,
0xbe49bfff,0x3fa2bfc6,0xbff53f15,0x3f71bfe2,0x3f843fdc,0xbf983fce,0x3fbebfac,0xbf5b3fe7,0x4000,0xc000,0xc000,0xc0000000,
0xbfb5bfb5,0x3f443fed,0x3fb53fb5,0x3fedbf44,0x40000000,0xbfb5bfb5,0xc0000000,0xbfb53fb5,0xbfb53fb5,0x3fed3f44,0x3fb5bfb5,0x3f44bfed,
0xbf44bfed,0x3f443fed,0x3ec83ffb,0x3ffbbec8,0x3fe73f5b,0xbfacbfbe,0xbfcebf98,0xbfdc3f84,0xbff53f15,0x3fe23f71,0x3fffbe49,0x3fa2bfc6,
0x3f84bfdc,0xbffdbe96,0xbfac3fbe,0xbf2c3ff1,0x3fb53fb5,0xbfb5bfb5,0xbf44bfed,0xbfed3f44,0xbfffbe49,0x3fe23f71,0x3fe23f71,0x3fc6bfa2,
0x3fd5bf8e,0xbffbbec8,0xbffb3ec8,0xbf8e3fd5,0xbf153ff5,0x3fffbe49,0x3fa2bfc6,0x3f15bff5,0xbfedbf44,0x3fed3f44,0x3f8e3fd5,0x3fd5bf8e,
0x3ff8bef9,0xbffdbe96,0xbff1bf2c,0xbfac3fbe,0xbfa23fc6,0x3fffbe49,0x3ff5bf15,0x3f71bfe2,0x3dc9c000,0xbff13f2c,0xbf983fce,0xbef93ff8,
0x40000000,0xc0000000,0xbfb5bfb5,0xbfb53fb5,0xbfd53f8e,0x3ffbbec8,0x3ffb3ec8,0x3f8ebfd5,0x3f44bfed,0xbfed3f44,0xbfed3f44,0xbf443fed,
0x3ec83ffb,0x3fd5bf8e,0x3f8ebfd5,0x3ec8bffb,0xbfed3f44,0x3fedbf44,0x3fd53f8e,0x3f8ebfd5,0x3f98bfce,0xbfdc3f84,0xc000bdc9,0xbf5b3fe7,
0xbe493fff,0x3fc6bfa2,0x3fe2bf71,0x3f15bff5,0xbf5bbfe7,0xbfac3fbe,0xbf843fdc,0xbe963ffd,0x3fb5bfb5,0xbfb53fb5,0xbfedbf44,0xbf443fed,
0xbf153ff5,0x3fa2bfc6,0x3fffbe49,0x3f15bff5,0xbec8bffb,0xbf8e3fd5,0xbfd53f8e,0xbec83ffb,0x3fa23fc6,0x3f71bfe2,0x3f71bfe2,0x3e49bfff,
0xbf443fed,0x3f44bfed,0x3ffb3ec8,0x3ec8bffb,0xbdc9c000,0xbf2c3ff1,0xbff83ef9,0xbe963ffd,0x3f713fe2,0x3f15bff5,0x3fc6bfa2,0x3e49bfff,
0xbfcebf98,0xbef93ff8,0xbf5b3fe7,0xbdc94000,0x3f803f80,0x3f803f80,0x4000,0xc0000000,0xc000,0x3f44bfed,0xc000,0x3fed3f44,
0x4000,0xbfb53fb5,0x4000,0xbfb5bfb5,0xc000,0x3fedbf44,0xc000,0x3f443fed,0xbf803f80,0xbf803f80,0xbec83ffb,0xbffbbec8,
0x3dc9c000,0x3f5bbfe7,0x3ef9bff8,0x3fce3f98,0xbe493fff,0xbfc63fa2,0xbf153ff5,0xbf71bfe2,0x3e96bffd,0x3ff8bef9,0x3f2cbff1,0x3dc94000,
0x3f803f80,0x3f803f80,0xbf443fed,0xbfedbf44,0x3e49bfff,0x3f71bfe2,0x3f71bfe2,0x3fa23fc6,0xbec83ffb,0xbfd53f8e,0xbf8e3fd5,0xbec8bffb,
0x3f15bff5,0x3fffbe49,0x3fa2bfc6,0xbf153ff5,0xbf803f80,0xbf803f80,0xbf8e3fd5,0xbfd5bf8e,0x3e96bffd,0x3f84bfdc,0x3facbfbe,0x3f5b3fe7,
0xbf153ff5,0xbfe23f71,0xbfc63fa2,0x3e49bfff,0x3f5bbfe7,0x40003dc9,0x3fdcbf84,0xbf983fce,0x3f803f80,0x3f803f80,0xbfb53fb5,0xbfb5bfb5,
0x3ec8bffb,0x3f8ebfd5,0x3fd5bf8e,0x3ec83ffb,0xbf443fed,0xbfed3f44,0xbfed3f44,0x3f44bfed,0x3f8ebfd5,0x3ffb3ec8,0x3ffbbec8,0xbfd53f8e,
0xbf803f80,0xbf803f80,0xbfd53f8e,0xbf8ebfd5,0x3ef9bff8,0x3f98bfce,0x3ff1bf2c,0xbdc94000,0xbf713fe2,0xbff53f15,0xbfff3e49,0x3fa2bfc6,
0x3facbfbe,0x3ff13f2c,0x3ffd3e96,0xbff83ef9,0x3f803f80,0x3f803f80,0xbfed3f44,0xbf44bfed,0x3f15bff5,0x3fa2bfc6,0x3fffbe49,0xbf153ff5,
0xbf8e3fd5,0xbffb3ec8,0xbffbbec8,0x3fd5bf8e,0x3fc6bfa2,0x3fe23f71,0x3fe23f71,0xbfffbe49,0xbf803f80,0xbf803f80,0xbffb3ec8,0xbec8bffb,
0x3f2cbff1,0x3facbfbe,0x3ffd3e96,0xbf843fdc,0xbfa23fc6,0xbfff3e49,0xbfe2bf71,0x3ff5bf15,0x3fdcbf84,0x3fce3f98,0x3fac3fbe,0xbfe7bf5b,
0x4000,0xc000,0x4000,0x40000000,0xc000,0xbf443fed,0xc000,0xbfedbf44,0x4000,0x3fb5bfb5,0x4000,0x3fb53fb5,
0xc000,0xbfed3f44,0xc000,0xbf44bfed,0xbf443fed,0x3f44bfed,0xbf8e3fd5,0x3fd53f8e,0x3f5bbfe7,0xbfbe3fac,0x3f98bfce,0xbf84bfdc,
0xbf713fe2,0x3ff5bf15,0xbfa23fc6,0x3e493fff,0x3f84bfdc,0xbffdbe96,0x3facbfbe,0x3f2cbff1,0xbfb53fb5,0x3fb5bfb5,0xbfed3f44,0x3f443fed,
0x3fc6bfa2,0xbff53f15,0x3ff5bf15,0x3e49bfff,0xbfd53f8e,0x3ffb3ec8,0xbffb3ec8,0xbf8e3fd5,0x3fe2bf71,0xbfc6bfa2,0x3fffbe49,0x3fe2bf71,
0xbfed3f44,0x3fedbf44,0xbffbbec8,0xbec83ffb,0x3ff8bef9,0xbffdbe96,0x3ff13f2c,0x3facbfbe,0xbfff3e49,0x3fc63fa2,0xbfe2bf71,0xbff53f15,
0x40003dc9,0xbf2cbff1,0x3fce3f98,0x3ff83ef9,0xc0000000,0x40000000,0xbfb5bfb5,0xbfb53fb5,0x3ffb3ec8,0xbfd5bf8e,0x3f8e3fd5,0x3ffbbec8,
0xbfedbf44,0x3f443fed,0xbf44bfed,0xbfedbf44,0x3fd53f8e,0x3ec8bffb,0x3ec83ffb,0x3f8e3fd5,0xbfedbf44,0x3fed3f44,0xbec8bffb,0xbffb3ec8,
0x3fce3f98,0xbf84bfdc,0xbdc94000,0x3fe73f5b,0xbfa2bfc6,0xbe493fff,0x3f15bff5,0xbf71bfe2,0x3f5b3fe7,0x3facbfbe,0xbf843fdc,0xbe963ffd,
0xbfb5bfb5,0x3fb53fb5,0x3f44bfed,0xbfedbf44,0x3f713fe2,0xbe49bfff,0xbfa23fc6,0x3f713fe2,0xbec8bffb,0xbf8e3fd5,0x3fd5bf8e,0x3ec8bffb,
0xbe493fff,0x3ff5bf15,0xbff53f15,0xbfc63fa2,0xbf44bfed,0x3f443fed,0x3fd5bf8e,0xbf8ebfd5,0x3dc94000,0x3f2cbff1,0xbff83ef9,0xbe963ffd,
0x3f15bff5,0xbfe23f71,0x3fff3e49,0x3fc6bfa2,0xbf983fce,0x3ff83ef9,0xbfe7bf5b,0xc000bdc9,0x4000,0x4000,0x4000,0xc0000000,
0xc000,0x3f44bfed,0xc000,0x3fed3f44,0x4000,0xbfb53fb5,0x4000,0xbfb5bfb5,0xc000,0x3fedbf44,0xc000,0x3f443fed,
0xbfb53fb5,0xbfb53fb5,0xbfd53f8e,0xbf8ebfd5,0x3fbebfac,0x3ff1bf2c,0x3fdcbf84,0x3e963ffd,0xbfc63fa2,0xbfffbe49,0xbfe23f71,0x3f15bff5,
0x3fcebf98,0x3fdc3f84,0x3fe7bf5b,0xbfac3fbe,0xc0000000,0xc0000000,0xbfedbf44,0x3f44bfed,0x3fff3e49,0x3fe23f71,0x3fe23f71,0xbfc63fa2,
0xbffbbec8,0xbf8ebfd5,0xbfd5bf8e,0x3ffbbec8,0x3ff53f15,0x3e493fff,0x3fc63fa2,0xbff5bf15,0xbfb5bfb5,0xbfb5bfb5,0xbec8bffb,0x3ffbbec8,
0x3f983fce,0x3ef93ff8,0x3dc94000,0xbff1bf2c,0xbf71bfe2,0x3f15bff5,0x3e49bfff,0x3fa23fc6,0x3f2c3ff1,0xbfbe3fac,0xbef93ff8,0xbe96bffd,
0xc000,0xc000,0x3fb5bfb5,0x3fb53fb5,0xbec83ffb,0xbf8e3fd5,0xbfd53f8e,0xbec8bffb,0x3f44bfed,0x3fedbf44,0x3fedbf44,0xbf443fed,
0xbf8e3fd5,0xbffbbec8,0xbffb3ec8,0x3fd5bf8e,0x3fb5bfb5,0x3fb5bfb5,0x3ffb3ec8,0xbec83ffb,0xbfdc3f84,0xbffd3e96,0xbfe7bf5b,0x3fbebfac,
0x3ff5bf15,0x3fe23f71,0x3fc63fa2,0xbfff3e49,0xc0003dc9,0xbf5bbfe7,0xbf98bfce,0x3fdc3f84,0x40000000,0x40000000,0x3f443fed,0xbfed3f44,
0xbff5bf15,0xbfc6bfa2,0xbe49bfff,0x3ff53f15,0x3fd53f8e,0x3ec83ffb,0xbec83ffb,0xbf8ebfd5,0xbfa2bfc6,0x3f71bfe2,0x3f71bfe2,0xbe493fff,
0x3fb53fb5,0x3fb53fb5,0xbf8e3fd5,0xbfd5bf8e,0xbf5bbfe7,0xbdc9c000,0x3fcebf98,0x3ef93ff8,0x3e493fff,0xbfa23fc6,0xbff53f15,0x3f71bfe2,
0x3ef9bff8,0x3ffdbe96,0x40003dc9,0xbff13f2c,0x4000,0xc000,0x4000,0x40000000,0xc000,0xbf443fed,0xc000,0xbfedbf44,
0x4000,0x3fb5bfb5,0x4000,0x3fb53fb5,0xc000,0xbfed3f44,0xc000,0xbf44bfed,0xbfed3f44,0x3fedbf44,0xbffb3ec8,0x3ec83ffb,
0x3ff1bf2c,0xc000bdc9,0x3ffdbe96,0x3ef9bff8,0xbff53f15,0x3fe23f71,0xbfff3e49,0xbfa23fc6,0x3ff8bef9,0xbf98bfce,0x4000bdc9,0x3fe7bf5b,
0xbfb5bfb5,0x3fb53fb5,0xbf44bfed,0xbfed3f44,0x3fa23fc6,0xbf15bff5,0x3f153ff5,0x3fff3e49,0xbf8ebfd5,0xbec83ffb,0xbec8bffb,0xbfd5bf8e,
0x3f713fe2,0x3fa2bfc6,0x3e493fff,0x3f713fe2,0x3f44bfed,0xbf443fed,0x3fd5bf8e,0xbf8ebfd5,0xbf843fdc,0x3fcebf98,0xbfe73f5b,0x3dc94000,
0x3fa2bfc6,0xbfff3e49,0x3ff5bf15,0x3f71bfe2,0xbfbe3fac,0x3fe73f5b,0xbffd3e96,0xbfdc3f84,0x40000000,0xc0000000,0x3fb53fb5,0x3fb5bfb5,
0xbffbbec8,0x3fd53f8e,0xbf8ebfd5,0xbffb3ec8,0x3fed3f44,0xbf44bfed,0x3f443fed,0x3fed3f44,0xbfd5bf8e,0xbec83ffb,0xbec8bffb,0xbf8ebfd5,
0x3f443fed,0xbf44bfed,0xbf8e3fd5,0x3fd53f8e,0xbe96bffd,0xbef93ff8,0x3fbebfac,0xbf2cbff1,0xbe493fff,0x3fc6bfa2,0xbfe23f71,0xbf153ff5,
0x3f2cbff1,0xc0003dc9,0x3ff8bef9,0x3fcebf98,0xbfb53fb5,0x3fb5bfb5,0xbfedbf44,0xbf443fed,0x3fe2bf71,0xbfff3e49,0x3fc63fa2,0x3fe2bf71,
0xbffb3ec8,0x3fd53f8e,0xbf8ebfd5,0xbffbbec8,0x3fff3e49,0xbf15bff5,0x3f153ff5,0x3fa23fc6,0xbfedbf44,0x3fed3f44,0x3ec8bffb,0xbffbbec8,
0x3fbe3fac,0xbf5bbfe7,0xbf843fdc,0x3f983fce,0xbf71bfe2,0xbf153ff5,0x3fc6bfa2,0x3e49bfff,0x3e963ffd,0x3fdcbf84,0xbff13f2c,0xbfbe3fac,
0x4000,0x4000,0x4000,0xc0000000,0xc000,0x3f44bfed,0xc000,0x3fed3f44,0x4000,0xbfb53fb5,0x4000,0xbfb5bfb5,
0xc000,0x3fedbf44,0xc000,0x3f443fed,0xc0000000,0xc0000000,0xbffbbec8,0x3ec8bffb,0x40003dc9,0x3fe73f5b,0x3ff83ef9,0xbf983fce,
0xbfffbe49,0xbfa2bfc6,0xbff5bf15,0x3fe2bf71,0x3ffd3e96,0x3ef93ff8,0x3ff13f2c,0xc0003dc9,0xc000,0xc000,0x3f44bfed,0x3fed3f44,
0xbe493fff,0xbf713fe2,0xbf713fe2,0xbfa2bfc6,0x3ec8bffb,0x3fd5bf8e,0x3f8ebfd5,0x3ec83ffb,0xbf153ff5,0xbfff3e49,0xbfa23fc6,0x3f15bff5,
0x40000000,0x40000000,0x3fd53f8e,0xbf8e3fd5,0xbffdbe96,0xbfdcbf84,0xbfbebfac,0x3fe7bf5b,0x3ff53f15,0x3f713fe2,0x3fa23fc6,0xbfffbe49,
0xbfe7bf5b,0x3dc9c000,0xbf84bfdc,0x3fce3f98,0x4000,0x4000,0xbfb53fb5,0xbfb5bfb5,0x3ec8bffb,0x3f8ebfd5,0x3fd5bf8e,0x3ec83ffb,
0xbf443fed,0xbfed3f44,0xbfed3f44,0x3f44bfed,0x3f8ebfd5,0x3ffb3ec8,0x3ffbbec8,0xbfd53f8e,0xc0000000,0xc0000000,0xbf8ebfd5,0x3fd5bf8e,
0x3ff83ef9,0x3fce3f98,0x3f2c3ff1,0xc000bdc9,0xbfe2bf71,0xbf15bff5,0xbe49bfff,0x3fc63fa2,0x3fbe3fac,0xbf2c3ff1,0xbe963ffd,0xbef9bff8,
0xc000,0xc000,0x3fedbf44,0x3f443fed,0xbf153ff5,0xbfa23fc6,0xbfff3e49,0x3f15bff5,0x3f8ebfd5,0x3ffbbec8,0x3ffb3ec8,0xbfd53f8e,
0xbfc63fa2,0xbfe2bf71,0xbfe2bf71,0x3fff3e49,0x40000000,0x40000000,0x3ec83ffb,0xbffb3ec8,0xbff1bf2c,0xbfbebfac,0x3e96bffd,0x3fdc3f84,
0x3fc63fa2,0x3e493fff,0xbf713fe2,0xbf15bff5,0xbf84bfdc,0x3f98bfce,0x3fbebfac,0xbf5b3fe7,0x4000,0xc000,0x4000,0x40000000,
0xc000,0xbf443fed,0xc000,0xbfedbf44,0x4000,0x3fb5bfb5,0x4000,0x3fb53fb5,0xc000,0xbfed3f44,0xc000,0xbf44bfed,
0xbfedbf44,0x3fed3f44,0xbfd5bf8e,0xbf8e3fd5,0x3fe73f5b,0xbfacbfbe,0x3fce3f98,0x3fdcbf84,0xbfe2bf71,0x3f153ff5,0xbfc6bfa2,0xbfff3e49,
0x3fdc3f84,0x3e96bffd,0x3fbe3fac,0x3ff13f2c,0x3fb5bfb5,0xbfb53fb5,0x3fedbf44,0xbf44bfed,0xbfc63fa2,0x3ff5bf15,0xbff53f15,0xbe493fff,
0x3fd5bf8e,0xbffbbec8,0x3ffbbec8,0x3f8ebfd5,0xbfe23f71,0x3fc63fa2,0xbfff3e49,0xbfe23f71,0x3f443fed,0xbf44bfed,0xbec83ffb,0x3ffb3ec8,
0xbef9bff8,0xbe963ffd,0x3f2cbff1,0xbfbebfac,0x3e493fff,0x3fa2bfc6,0xbf713fe2,0x3f153ff5,0x3dc9c000,0xbff13f2c,0x3f98bfce,0x3ef9bff8,
0xc0000000,0x40000000,0xbfb5bfb5,0xbfb53fb5,0x3ffb3ec8,0xbfd5bf8e,0x3f8e3fd5,0x3ffbbec8,0xbfedbf44,0x3f443fed,0xbf44bfed,0xbfedbf44,
0x3fd53f8e,0x3ec8bffb,0x3ec83ffb,0x3f8e3fd5,0x3f44bfed,0xbf443fed,0x3ffbbec8,0xbec8bffb,0xbf983fce,0x3fdcbf84,0xc000bdc9,0xbf5b3fe7,
0x3fc6bfa2,0xbfffbe49,0x3ff53f15,0x3fe2bf71,0xbfe73f5b,0x3fbe3fac,0xbfdcbf84,0xbffdbe96,0x3fb53fb5,0xbfb5bfb5,0xbf443fed,0x3fed3f44,
0xbf71bfe2,0x3e493fff,0x3fa2bfc6,0xbf71bfe2,0x3ec83ffb,0x3f8ebfd5,0xbfd53f8e,0xbec83ffb,0x3e49bfff,0xbff53f15,0x3ff5bf15,0x3fc6bfa2,
0xbfed3f44,0x3fedbf44,0xbf8ebfd5,0xbfd53f8e,0x4000bdc9,0xbff1bf2c,0x3ef93ff8,0x3ffd3e96,0xbff5bf15,0x3f713fe2,0x3e49bfff,0xbfa2bfc6,
0x3fce3f98,0x3ef9bff8,0xbf5b3fe7,0xbdc94000,0x4000,0x4000,0x4000,0xc0000000,0xc000,0x3f44bfed,0xc000,0x3fed3f44,
0x4000,0xbfb53fb5,0x4000,0xbfb5bfb5,0xc000,0x3fedbf44,0xc000,0x3f443fed,0xbfb5bfb5,0xbfb5bfb5,0xbf8ebfd5,0x3fd5bf8e,
0x3fac3fbe,0x3f2c3ff1,0x3f843fdc,0xbffd3e96,0xbfa2bfc6,0x3e49bfff,0xbf71bfe2,0x3ff53f15,0x3f983fce,0xbf843fdc,0x3f5b3fe7,0xbfbebfac,
0x40000000,0x40000000,0x3fed3f44,0xbf443fed,0xbfffbe49,0xbfe2bf71,0xbfe2bf71,0x3fc6bfa2,0x3ffb3ec8,0x3f8e3fd5,0x3fd53f8e,0xbffb3ec8,
0xbff5bf15,0xbe49bfff,0xbfc6bfa2,0x3ff53f15,0xbfb53fb5,0xbfb53fb5,0xbffb3ec8,0xbec8bffb,0x3fcebf98,0x3ff8bef9,0x4000bdc9,0xbf2c3ff1,
0xbfe23f71,0xbff5bf15,0xbfffbe49,0x3fc6bfa2,0x3ff1bf2c,0x3fac3fbe,0x3ff83ef9,0xbffd3e96,0xc000,0xc000,0x3fb5bfb5,0x3fb53fb5,
0xbec83ffb,0xbf8e3fd5,0xbfd53f8e,0xbec8bffb,0x3f44bfed,0x3fedbf44,0x3fedbf44,0xbf443fed,0xbf8e3fd5,0xbffbbec8,0xbffb3ec8,0x3fd5bf8e,
0x3fb53fb5,0x3fb53fb5,0xbec83ffb,0xbffbbec8,0xbf84bfdc,0xbe96bffd,0x3f5bbfe7,0x3fac3fbe,0x3f153ff5,0xbf713fe2,0xbfa23fc6,0xbe49bfff,
0xbdc9c000,0x3fe7bf5b,0x3fcebf98,0xbf843fdc,0xc0000000,0xc0000000,0xbf44bfed,0x3fedbf44,0x3ff53f15,0x3fc63fa2,0x3e493fff,0xbff5bf15,
0xbfd5bf8e,0xbec8bffb,0x3ec8bffb,0x3f8e3fd5,0x3fa23fc6,0xbf713fe2,0xbf713fe2,0x3e49bfff,0x3fb5bfb5,0x3fb5bfb5,0x3fd53f8e,0xbf8e3fd5,
0xbfe73f5b,0xc0003dc9,0xbf98bfce,0x3ff8bef9,0x3fffbe49,0x3fc63fa2,0x3f153ff5,0xbfe2bf71,0xbff8bef9,0xbe96bffd,0x3dc9c000,0x3f2c3ff1,
0x4000,0xc000,0x4000,0x40000000,0xc000,0xbf443fed,0xc000,0xbfedbf44,0x4000,0x3fb5bfb5,0x4000,0x3fb53fb5,
0xc000,0xbfed3f44,0xc000,0xbf44bfed,0xbf44bfed,0x3f443fed,0xbec8bffb,0xbffb3ec8,0x3f2c3ff1,0x3dc9c000,0x3e963ffd,0x3ff83ef9,
0xbf15bff5,0xbf713fe2,0xbe49bfff,0xbfc6bfa2,0x3ef93ff8,0x3fcebf98,0x3dc94000,0x3f5b3fe7,0x3fb53fb5,0xbfb5bfb5,0x3f443fed,0x3fedbf44,
0xbfa2bfc6,0x3f153ff5,0xbf15bff5,0xbfffbe49,0x3f8e3fd5,0x3ec8bffb,0x3ec83ffb,0x3fd53f8e,0xbf71bfe2,0xbfa23fc6,0xbe49bfff,0xbf71bfe2,
0xbfedbf44,0x3fed3f44,0xbf8ebfd5,0xbfd53f8e,0x3fdc3f84,0xbf98bfce,0x3f5b3fe7,0x4000bdc9,0xbfc6bfa2,0x3e493fff,0xbf15bff5,0xbfe2bf71,
0x3fac3fbe,0x3f5bbfe7,0x3e963ffd,0x3f843fdc,0x40000000,0xc0000000,0x3fb53fb5,0x3fb5bfb5,0xbffbbec8,0x3fd53f8e,0xbf8ebfd5,0xbffb3ec8,
0x3fed3f44,0xbf44bfed,0x3f443fed,0x3fed3f44,0xbfd5bf8e,0xbec83ffb,0xbec8bffb,0xbf8ebfd5,0xbfed3f44,0x3fedbf44,0xbfd5bf8e,0xbf8e3fd5,
0x3ffdbe96,0xbff8bef9,0x3fac3fbe,0x3ff1bf2c,0xbfffbe49,0x3fa23fc6,0xbf71bfe2,0xbff5bf15,0x3ff13f2c,0xbdc9c000,0x3ef93ff8,0x3f983fce,
0x3fb5bfb5,0xbfb53fb5,0x3fed3f44,0x3f44bfed,0xbfe23f71,0x3fffbe49,0xbfc6bfa2,0xbfe23f71,0x3ffbbec8,0xbfd5bf8e,0x3f8e3fd5,0x3ffb3ec8,
0xbfffbe49,0x3f153ff5,0xbf15bff5,0xbfa2bfc6,0xbf443fed,0x3f44bfed,0xbffbbec8,0xbec83ffb,0x3facbfbe,0xbfe73f5b,0x3fdc3f84,0x3fcebf98,
0xbfe23f71,0x3ff53f15,0xbfa2bfc6,0xbfffbe49,0x3ffdbe96,0xbf84bfdc,0x3f2c3ff1,0x3fac3fbe,0x3f803f80,0x3f803f80,0xc000,0x40000000,
0x3fb5bfb5,0x3fedbf44,0xbfb53fb5,0xbf44bfed,0xc0000000,0xbfb5bfb5,0x40000000,0xbfb53fb5,0x3fb53fb5,0xbf443fed,0xbfb5bfb5,0x3fed3f44,
0xbf803f80,0xbf803f80,0x3ec8bffb,0x3ffb3ec8,0x3fbebfac,0x3ff1bf2c,0xbfdc3f84,0xbe96bffd,0xbfffbe49,0xbfa2bfc6,0x3ff53f15,0xbfe23f71,
0x3f983fce,0xbf843fdc,0xbf5bbfe7,0x3fbe3fac,0x3f803f80,0x3f803f80,0x3f44bfed,0x3fed3f44,0x3fc6bfa2,0x3ff5bf15,0xbff53f15,0x3e49bfff,
0xbffbbec8,0xbf8ebfd5,0x3fd53f8e,0xbffb3ec8,0x3f713fe2,0xbfa23fc6,0xbe49bfff,0x3f713fe2,0xbf803f80,0xbf803f80,0x3f8ebfd5,0x3fd53f8e,
0x3fcebf98,0x3ff8bef9,0xc0003dc9,0x3f2cbff1,0xbff5bf15,0xbf71bfe2,0x3fa23fc6,0xbfffbe49,0x3f2c3ff1,0xbfbe3fac,0x3ef9bff8,0x3e963ffd,
0x3f803f80,0x3f803f80,0x3fb5bfb5,0x3fb53fb5,0x3fd5bf8e,0x3ffbbec8,0xbffbbec8,0x3f8ebfd5,0xbfedbf44,0xbf44bfed,0x3f443fed,0xbfedbf44,
0x3ec83ffb,0xbfd53f8e,0x3f8ebfd5,0xbec83ffb,0xbf803f80,0xbf803f80,0x3fd5bf8e,0x3f8e3fd5,0x3fdcbf84,0x3ffdbe96,0xbfe7bf5b,0x3fbebfac,
0xbfe2bf71,0xbf15bff5,0x3e493fff,0xbfc6bfa2,0x3dc94000,0xbfe73f5b,0x3fcebf98,0xbf843fdc,0x3f803f80,0x3f803f80,0x3fedbf44,0x3f443fed,
0x3fe2bf71,0x3fffbe49,0xbfc6bfa2,0x3fe2bf71,0xbfd5bf8e,0xbec8bffb,0xbec83ffb,0xbf8ebfd5,0xbe493fff,0xbff53f15,0x3ff5bf15,0xbfc63fa2,
0xbf803f80,0xbf803f80,0x3ffbbec8,0x3ec83ffb,0x3fe7bf5b,0x4000bdc9,0xbf98bfce,0x3ff8bef9,0xbfc6bfa2,0xbe49bfff,0xbf713fe2,0xbf15bff5,
0xbef93ff8,0xbffd3e96,0x40003dc9,0xbff13f2c,0x4000,0xc000,0xc000,0xc0000000,0x3fb5bfb5,0xbfed3f44,0xbfb53fb5,0x3f443fed,
0xc0000000,0x3fb53fb5,0x40000000,0x3fb5bfb5,0x3fb53fb5,0x3f44bfed,0xbfb5bfb5,0xbfedbf44,0xbf443fed,0x3f44bfed,0x3f8ebfd5,0xbfd5bf8e,
0x3ff1bf2c,0xc000bdc9,0xbffd3e96,0xbef93ff8,0xbfe2bf71,0x3f153ff5,0x3fc63fa2,0x3fffbe49,0x3ef93ff8,0x3fcebf98,0xbdc9c000,0xbf5bbfe7,
0xbfb53fb5,0x3fb5bfb5,0x3fedbf44,0xbf44bfed,0x3fff3e49,0xbfe2bf71,0xbfe2bf71,0xbfc63fa2,0xbf8ebfd5,0xbec83ffb,0x3ec83ffb,0x3fd53f8e,
0xbf153ff5,0x3fffbe49,0x3fa2bfc6,0x3f15bff5,0xbfed3f44,0x3fedbf44,0x3ffb3ec8,0x3ec8bffb,0x3fdc3f84,0xbf98bfce,0xbf5bbfe7,0xc0003dc9,
0xbe49bfff,0xbfa23fc6,0xbf713fe2,0x3f153ff5,0xbfbe3fac,0x3fe73f5b,0x3ffdbe96,0x3fdcbf84,0xc0000000,0x40000000,0x3fb53fb5,0x3fb5bfb5,
0x3f8e3fd5,0xbec8bffb,0x3ec8bffb,0xbfd5bf8e,0x3f44bfed,0xbfed3f44,0xbfed3f44,0xbf443fed,0xbffb3ec8,0x3f8e3fd5,0x3fd53f8e,0x3ffb3ec8,
0xbfedbf44,0x3fed3f44,0x3ec83ffb,0x3ffbbec8,0x3e963ffd,0x3ef9bff8,0x3fbebfac,0xbf2cbff1,0x3fc6bfa2,0xbfffbe49,0xbff5bf15,0xbfe23f71,
0xbff1bf2c,0x3dc94000,0x3ef93ff8,0x3f983fce,0xbfb5bfb5,0x3fb53fb5,0xbf443fed,0x3fed3f44,0xbf153ff5,0x3fa2bfc6,0x3fffbe49,0x3f15bff5,
0x3ffbbec8,0xbfd5bf8e,0xbf8ebfd5,0xbffbbec8,0xbfa2bfc6,0xbf713fe2,0xbf713fe2,0xbe493fff,0xbf44bfed,0x3f443fed,0xbfd53f8e,0x3f8e3fd5,
0xbfac3fbe,0x3fe7bf5b,0x3fdc3f84,0x3fcebf98,0x3ff53f15,0xbf71bfe2,0x3e49bfff,0xbfa2bfc6,0xbe96bffd,0xbfdc3f84,0xbff13f2c,0xbfbe3fac,
0x4000,0x4000,0xc000,0x40000000,0x3fb5bfb5,0x3fedbf44,0xbfb53fb5,0xbf44bfed,0xc0000000,0xbfb5bfb5,0x40000000,0xbfb53fb5,
0x3fb53fb5,0xbf443fed,0xbfb5bfb5,0x3fed3f44,0xbfb53fb5,0xbfb53fb5,0x3fd5bf8e,0x3f8e3fd5,0x40003dc9,0x3fe73f5b,0xbff8bef9,0x3f98bfce,
0xbfa2bfc6,0x3e49bfff,0x3f713fe2,0xbff5bf15,0xbe963ffd,0xbff83ef9,0x3f2cbff1,0x3dc94000,0xc0000000,0xc0000000,0x3fed3f44,0xbf443fed,
0x3fa23fc6,0x3f153ff5,0xbf15bff5,0x3fff3e49,0x3ec8bffb,0x3fd5bf8e,0xbf8e3fd5,0xbec8bffb,0xbfe23f71,0xbfc6bfa2,0x3fffbe49,0xbfe23f71,
0xbfb5bfb5,0xbfb5bfb5,0x3ec83ffb,0xbffb3ec8,0xbe963ffd,0xbf843fdc,0x3facbfbe,0x3f5b3fe7,0x3fe2bf71,0x3ff53f15,0xbfffbe49,0x3fc6bfa2,
0xbfe7bf5b,0x3dc9c000,0x3f843fdc,0xbfcebf98,0xc000,0xc000,0xbfb53fb5,0xbfb5bfb5,0xbfd53f8e,0xbffb3ec8,0x3ffb3ec8,0xbf8e3fd5,
0x3fed3f44,0x3f443fed,0xbf44bfed,0x3fed3f44,0xbec8bffb,0x3fd5bf8e,0xbf8e3fd5,0x3ec8bffb,0x3fb5bfb5,0x3fb5bfb5,0xbffbbec8,0x3ec8bffb,
0xbff8bef9,0xbfcebf98,0x3f2c3ff1,0xc000bdc9,0x3f153ff5,0xbf713fe2,0x3fa2bfc6,0x3e493fff,0x3facbfbe,0x3ff13f2c,0xbffdbe96,0x3ff8bef9,
0x40000000,0x40000000,0xbf44bfed,0x3fedbf44,0xbf71bfe2,0xbe49bfff,0xbfa23fc6,0xbf71bfe2,0xbf8e3fd5,0xbffb3ec8,0x3ffb3ec8,0xbfd53f8e,
0x3fff3e49,0x3f153ff5,0xbf15bff5,0x3fa23fc6,0x3fb53fb5,0x3fb53fb5,0x3f8ebfd5,0x3fd53f8e,0x3f2cbff1,0x3facbfbe,0xbffdbe96,0x3f84bfdc,
0xbfff3e49,0xbfc6bfa2,0x3f153ff5,0xbfe2bf71,0x3f843fdc,0xbf983fce,0x3fbebfac,0xbf5b3fe7,0x4000,0xc000,0xc000,0xc0000000,
0x3fb5bfb5,0xbfed3f44,0xbfb53fb5,0x3f443fed,0xc0000000,0x3fb53fb5,0x40000000,0x3fb5bfb5,0x3fb53fb5,0x3f44bfed,0xbfb5bfb5,0xbfedbf44,
0xbfed3f44,0x3fedbf44,0x3ffbbec8,0xbec8bffb,0x3fe73f5b,0xbfacbfbe,0xbfcebf98,0xbfdc3f84,0xbf15bff5,0xbf713fe2,0x3e493fff,0x3fc63fa2,
0xbf843fdc,0x3ffd3e96,0x3facbfbe,0x3f2cbff1,0xbfb5bfb5,0x3fb53fb5,0x3f443fed,0x3fedbf44,0xbe493fff,0x3f71bfe2,0x3f71bfe2,0xbfa2bfc6,
0x3fd5bf8e,0xbffbbec8,0xbffb3ec8,0xbf8e3fd5,0xbff5bf15,0x3e493fff,0x3fc63fa2,0x3ff53f15,0x3f44bfed,0xbf443fed,0xbfd53f8e,0x3f8e3fd5,
0xbff83ef9,0x3ffd3e96,0x3ff13f2c,0x3facbfbe,0x3fc63fa2,0xbe49bfff,0xbf15bff5,0xbfe2bf71,0x3dc9c000,0xbff13f2c,0xbf983fce,0xbef93ff8,
0x40000000,0xc0000000,0xbfb5bfb5,0xbfb53fb5,0xbf8ebfd5,0x3ec83ffb,0xbec83ffb,0x3fd53f8e,0xbf443fed,0x3fedbf44,0x3fedbf44,0x3f44bfed,
0x3ffbbec8,0xbf8ebfd5,0xbfd5bf8e,0xbffbbec8,0x3f443fed,0xbf44bfed,0x3f8ebfd5,0xbfd5bf8e,0x3f98bfce,0xbfdc3f84,0xc000bdc9,0xbf5b3fe7,
0xbfffbe49,0x3fa23fc6,0x3f713fe2,0x3ff53f15,0x3f5b3fe7,0x3facbfbe,0x3f84bfdc,0x3e96bffd,0xbfb53fb5,0x3fb5bfb5,0x3fed3f44,0x3f44bfed,
0x3ff53f15,0xbfc6bfa2,0xbe49bfff,0xbff5bf15,0xbec8bffb,0xbf8e3fd5,0xbfd53f8e,0xbec83ffb,0xbfc63fa2,0x3fe23f71,0x3fe23f71,0x3fff3e49,
0xbfedbf44,0x3fed3f44,0xbec83ffb,0x3ffb3ec8,0x3dc94000,0x3f2cbff1,0x3ff8bef9,0x3e96bffd,0x3fe2bf71,0xbff5bf15,0xbfa2bfc6,0xbfffbe49,
0xbfcebf98,0xbef93ff8,0xbf5b3fe7,0xbdc94000,0x4000,0x4000,0xc000,0x40000000,0x3fb5bfb5,0x3fedbf44,0xbfb53fb5,0xbf44bfed,
0xc0000000,0xbfb5bfb5,0x40000000,0xbfb53fb5,0x3fb53fb5,0xbf443fed,0xbfb5bfb5,0x3fed3f44,0xc0000000,0xc0000000,0x3ffb3ec8,0xbec83ffb,
0x3fac3fbe,0x3f2c3ff1,0xbf84bfdc,0x3ffdbe96,0x3e49bfff,0x3fc6bfa2,0xbf153ff5,0xbf71bfe2,0xbfce3f98,0xbfdcbf84,0x3fe7bf5b,0xbfac3fbe,
0xc000,0xc000,0xbf443fed,0xbfedbf44,0xbfc63fa2,0xbff53f15,0x3ff5bf15,0xbe493fff,0x3ffb3ec8,0x3f8e3fd5,0xbfd5bf8e,0x3ffbbec8,
0xbf71bfe2,0x3fa2bfc6,0x3e493fff,0xbf71bfe2,0x40000000,0x40000000,0xbfd5bf8e,0x3f8ebfd5,0xbf98bfce,0xbef9bff8,0x3dc94000,0xbff1bf2c,
0xbf153ff5,0xbfe23f71,0x3fc6bfa2,0xbe493fff,0x3ff1bf2c,0x3fac3fbe,0xbff8bef9,0x3ffdbe96,0x4000,0x4000,0x3fb5bfb5,0x3fb53fb5,
0x3fd5bf8e,0x3ffbbec8,0xbffbbec8,0x3f8ebfd5,0xbfedbf44,0xbf44bfed,0x3f443fed,0xbfedbf44,0x3ec83ffb,0xbfd53f8e,0x3f8ebfd5,0xbec83ffb,
0xc0000000,0xc0000000,0x3f8e3fd5,0xbfd53f8e,0x3f843fdc,0x3e963ffd,0x3f5bbfe7,0x3fac3fbe,0x3f71bfe2,0x3ff5bf15,0xbfff3e49,0x3fa2bfc6,
0xc0003dc9,0xbf5bbfe7,0x3f983fce,0xbfdcbf84,0xc000,0xc000,0xbfed3f44,0xbf44bfed,0xbfe23f71,0xbfff3e49,0x3fc63fa2,0xbfe23f71,
0x3fd53f8e,0x3ec83ffb,0x3ec8bffb,0x3f8e3fd5,0x3e49bfff,0x3ff5bf15,0xbff53f15,0x3fc6bfa2,0x40000000,0x40000000,0xbec8bffb,0x3ffbbec8,
0xbf5bbfe7,0xbdc9c000,0xbfce3f98,0xbef9bff8,0xbfa23fc6,0xbfff3e49,0x3fe23f71,0xbff53f15,0x3ff83ef9,0x3e963ffd,0x3dc9c000,0x3f2c3ff1,
0x4000,0xc000,0xc000,0xc0000000,0x3fb5bfb5,0xbfed3f44,0xbfb53fb5,0x3f443fed,0xc0000000,0x3fb53fb5,0x40000000,0x3fb5bfb5,
0x3fb53fb5,0x3f44bfed,0xbfb5bfb5,0xbfedbf44,0xbfedbf44,0x3fed3f44,0x3fd53f8e,0x3f8ebfd5,0x3f2c3ff1,0x3dc9c000,0xbe96bffd,0xbff8bef9,
0x3f71bfe2,0xbff53f15,0xbfa23fc6,0x3e493fff,0xbff83ef9,0x3f983fce,0x4000bdc9,0x3fe7bf5b,0x3fb5bfb5,0xbfb53fb5,0xbfed3f44,0x3f443fed,
0xbfffbe49,0x3fe23f71,0x3fe23f71,0x3fc6bfa2,0x3f8e3fd5,0x3ec8bffb,0xbec8bffb,0xbfd5bf8e,0x3f15bff5,0xbfff3e49,0xbfa23fc6,0xbf153ff5,
0x3f443fed,0xbf44bfed,0x3ec8bffb,0xbffbbec8,0x3f84bfdc,0xbfce3f98,0xbfe73f5b,0x3dc94000,0xbfff3e49,0x3fc63fa2,0x3fe23f71,0x3ff5bf15,
0x3fac3fbe,0x3f5bbfe7,0xbe96bffd,0xbf84bfdc,0xc0000000,0x40000000,0x3fb53fb5,0x3fb5bfb5,0x3f8e3fd5,0xbec8bffb,0x3ec8bffb,0xbfd5bf8e,
0x3f44bfed,0xbfed3f44,0xbfed3f44,0xbf443fed,0xbffb3ec8,0x3f8e3fd5,0x3fd53f8e,0x3ffb3ec8,0x3f44bfed,0xbf443fed,0xbffb3ec8,0x3ec83ffb,
0xbffd3e96,0x3ff83ef9,0x3fac3fbe,0x3ff1bf2c,0x3fa23fc6,0x3e49bfff,0x3f15bff5,0xbf71bfe2,0x3f2cbff1,0xc0003dc9,0xbff83ef9,0xbfce3f98,
0x3fb53fb5,0xbfb5bfb5,0x3f44bfed,0xbfedbf44,0x3f15bff5,0xbfa23fc6,0xbfff3e49,0xbf153ff5,0xbffb3ec8,0x3fd53f8e,0x3f8e3fd5,0x3ffb3ec8,
0x3fa23fc6,0x3f71bfe2,0x3f71bfe2,0x3e49bfff,0xbfed3f44,0x3fedbf44,0x3f8e3fd5,0x3fd5bf8e,0x3fbe3fac,0xbf5bbfe7,0x3f84bfdc,0xbf98bfce,
0x3f15bff5,0xbfe23f71,0xbfffbe49,0xbfc63fa2,0xbffd3e96,0x3f843fdc,0x3f2c3ff1,0x3fac3fbe,0x4000,0x4000,0xc000,0x40000000,
0x3fb5bfb5,0x3fedbf44,0xbfb53fb5,0xbf44bfed,0xc0000000,0xbfb5bfb5,0x40000000,0xbfb53fb5,0x3fb53fb5,0xbf443fed,0xbfb5bfb5,0x3fed3f44,
0xbfb5bfb5,0xbfb5bfb5,0x3f8e3fd5,0xbfd53f8e,0xbdc94000,0xbf5b3fe7,0x3ef9bff8,0x3fce3f98,0x3fc6bfa2,0x3fff3e49,0xbfe23f71,0x3f15bff5,
0xbffdbe96,0xbef9bff8,0x3ff13f2c,0xc0003dc9,0x40000000,0x40000000,0xbfedbf44,0x3f44bfed,0xbfa2bfc6,0xbf15bff5,0x3f153ff5,0xbfffbe49,
0xbec83ffb,0xbfd53f8e,0x3f8ebfd5,0x3ec83ffb,0x3fe2bf71,0x3fc63fa2,0xbfff3e49,0x3fe2bf71,0xbfb53fb5,0xbfb53fb5,0x3ffbbec8,0x3ec83ffb,
0x3ffd3e96,0x3fdc3f84,0xbfbebfac,0x3fe7bf5b,0xbf71bfe2,0x3f15bff5,0xbe493fff,0xbfa2bfc6,0xbf5b3fe7,0xc000bdc9,0x3fdcbf84,0xbf983fce,
0xc000,0xc000,0xbfb53fb5,0xbfb5bfb5,0xbfd53f8e,0xbffb3ec8,0x3ffb3ec8,0xbf8e3fd5,0x3fed3f44,0x3f443fed,0xbf44bfed,0x3fed3f44,
0xbec8bffb,0x3fd5bf8e,0xbf8e3fd5,0x3ec8bffb,0x3fb53fb5,0x3fb53fb5,0x3ec8bffb,0x3ffb3ec8,0x3ef9bff8,0x3f98bfce,0xbff13f2c,0x3dc9c000,
0xbff53f15,0xbfe2bf71,0x3fc63fa2,0xbfff3e49,0x3fbe3fac,0xbf2c3ff1,0x3e96bffd,0x3ef93ff8,0xc0000000,0xc0000000,0x3f443fed,0xbfed3f44,
0x3f713fe2,0x3e493fff,0x3fa2bfc6,0x3f713fe2,0x3f8ebfd5,0x3ffbbec8,0xbffbbec8,0x3fd5bf8e,0xbfffbe49,0xbf15bff5,0x3f153ff5,0xbfa2bfc6,
0x3fb5bfb5,0x3fb5bfb5,0xbfd5bf8e,0x3f8ebfd5,0xbff1bf2c,0xbfbebfac,0xbe963ffd,0xbfdcbf84,0x3e493fff,0xbfa23fc6,0x3ff5bf15,0xbf713fe2,
0x3fdcbf84,0x3fce3f98,0xbfacbfbe,0x3fe73f5b,0x4000,0xc000,0xc000,0xc0000000,0x3fb5bfb5,0xbfed3f44,0xbfb53fb5,0x3f443fed,
0xc0000000,0x3fb53fb5,0x40000000,0x3fb5bfb5,0x3fb53fb5,0x3f44bfed,0xbfb5bfb5,0xbfedbf44,0xbf44bfed,0x3f443fed,0x3ec83ffb,0x3ffbbec8,
0xbf5b3fe7,0x3fbebfac,0x3f98bfce,0xbf84bfdc,0x3ff5bf15,0xbfe2bf71,0xbfff3e49,0xbfa23fc6,0xbfdcbf84,0xbe963ffd,0x3fbe3fac,0x3ff13f2c,
0x3fb53fb5,0xbfb5bfb5,0xbf44bfed,0xbfed3f44,0x3e49bfff,0xbf713fe2,0xbf713fe2,0x3fa23fc6,0xbfd53f8e,0x3ffb3ec8,0x3ffbbec8,0x3f8ebfd5,
0x3ff53f15,0xbe49bfff,0xbfc6bfa2,0xbff5bf15,0xbfedbf44,0x3fed3f44,0x3f8e3fd5,0x3fd5bf8e,0x3ef93ff8,0x3e96bffd,0x3f2cbff1,0xbfbebfac,
0x3fa2bfc6,0xbfff3e49,0xbff53f15,0xbf713fe2,0xc000bdc9,0x3f2c3ff1,0x3fce3f98,0x3ff83ef9,0x40000000,0xc0000000,0xbfb5bfb5,0xbfb53fb5,
0xbf8ebfd5,0x3ec83ffb,0xbec83ffb,0x3fd53f8e,0xbf443fed,0x3fedbf44,0x3fedbf44,0x3f44bfed,0x3ffbbec8,0xbf8ebfd5,0xbfd5bf8e,0xbffbbec8,
0xbfed3f44,0x3fedbf44,0x3fd53f8e,0x3f8ebfd5,0x3fce3f98,0xbf84bfdc,0x3dc9c000,0xbfe7bf5b,0x3e49bfff,0xbfc63fa2,0xbfe23f71,0xbf153ff5,
0xbfe73f5b,0x3fbe3fac,0x3fdc3f84,0x3ffd3e96,0x3fb5bfb5,0xbfb53fb5,0xbfedbf44,0xbf443fed,0xbff5bf15,0x3fc63fa2,0x3e493fff,0x3ff53f15,
0x3ec83ffb,0x3f8ebfd5,0x3fd5bf8e,0x3ec8bffb,0x3fc6bfa2,0xbfe2bf71,0xbfe2bf71,0xbfffbe49,0xbf443fed,0x3f44bfed,0x3ffb3ec8,0x3ec8bffb,
0x4000bdc9,0xbff1bf2c,0xbef9bff8,0xbffdbe96,0xbf71bfe2,0xbf153ff5,0xbfc63fa2,0xbe493fff,0xbf983fce,0x3ff83ef9,0x3fe73f5b,0x40003dc9,
0x3f803f80,0x3f803f80,0x4000,0xc0000000,0x40000000,0x3fed3f44,0x40000000,0xbf443fed,0xc000,0x3fb5bfb5,0xc000,0x3fb53fb5,
0xc0000000,0xbf44bfed,0xc0000000,0x3fedbf44,0xbf803f80,0xbf803f80,0xbec83ffb,0xbffbbec8,0x40003dc9,0x3fe73f5b,0x3ff83ef9,0xbf983fce,
0x3e49bfff,0x3fc6bfa2,0x3f15bff5,0x3f713fe2,0xbffdbe96,0xbef9bff8,0xbff1bf2c,0x4000bdc9,0x3f803f80,0x3f803f80,0xbf443fed,0xbfedbf44,
0x3fff3e49,0x3fe23f71,0x3fe23f71,0xbfc63fa2,0x3ec8bffb,0x3fd5bf8e,0x3f8ebfd5,0x3ec83ffb,0xbff5bf15,0xbe49bfff,0xbfc6bfa2,0x3ff53f15,
0xbf803f80,0xbf803f80,0xbf8e3fd5,0xbfd5bf8e,0x3ffd3e96,0x3fdc3f84,0x3fbe3fac,0xbfe73f5b,0x3f15bff5,0x3fe2bf71,0x3fc6bfa2,0xbe493fff,
0xbfe7bf5b,0x3dc9c000,0xbf84bfdc,0x3fce3f98,0x3f803f80,0x3f803f80,0xbfb53fb5,0xbfb5bfb5,0x3ffb3ec8,0x3fd53f8e,0x3f8e3fd5,0xbffb3ec8,
0x3f44bfed,0x3fedbf44,0x3fedbf44,0xbf443fed,0xbfd5bf8e,0x3ec8bffb,0xbec8bffb,0x3f8e3fd5,0xbf803f80,0xbf803f80,0xbfd53f8e,0xbf8ebfd5,
0x3ff83ef9,0x3fce3f98,0x3f2c3ff1,0xc000bdc9,0x3f71bfe2,0x3ff5bf15,0x3fffbe49,0xbfa23fc6,0xbfbebfac,0x3f2cbff1,0x3e96bffd,0x3ef93ff8,
0x3f803f80,0x3f803f80,0xbfed3f44,0xbf44bfed,0x3ff53f15,0x3fc63fa2,0x3e493fff,0xbff5bf15,0x3f8ebfd5,0x3ffbbec8,0x3ffb3ec8,0xbfd53f8e,
0xbfa2bfc6,0x3f71bfe2,0x3f71bfe2,0xbe493fff,0xbf803f80,0xbf803f80,0xbffb3ec8,0xbec8bffb,0x3ff13f2c,0x3fbe3fac,0xbe963ffd,0xbfdcbf84,
0x3fa2bfc6,0x3fffbe49,0x3fe23f71,0xbff53f15,0xbf84bfdc,0x3f98bfce,0x3fbebfac,0xbf5b3fe7,0x4000,0xc000,0x4000,0x40000000,
0x40000000,0xbfedbf44,0x40000000,0x3f44bfed,0xc000,0xbfb53fb5,0xc000,0xbfb5bfb5,0xc0000000,0x3f443fed,0xc0000000,0xbfed3f44,
0xbf443fed,0x3f44bfed,0xbf8e3fd5,0x3fd53f8e,0x3fe73f5b,0xbfacbfbe,0x3fce3f98,0x3fdcbf84,0x3f71bfe2,0xbff53f15,0x3fa2bfc6,0xbe49bfff,
0xbfdcbf84,0xbe963ffd,0xbfbebfac,0xbff1bf2c,0xbfb53fb5,0x3fb5bfb5,0xbfed3f44,0x3f443fed,0x3fa23fc6,0xbf15bff5,0x3f153ff5,0x3fff3e49,
0x3fd5bf8e,0xbffbbec8,0x3ffbbec8,0x3f8ebfd5,0xbf71bfe2,0xbfa23fc6,0xbe49bfff,0xbf71bfe2,0xbfed3f44,0x3fedbf44,0xbffbbec8,0xbec83ffb,
0x3ef93ff8,0x3e96bffd,0xbf2c3ff1,0x3fbe3fac,0x3fffbe49,0xbfc6bfa2,0x3fe23f71,0x3ff5bf15,0x3dc9c000,0xbff13f2c,0x3f98bfce,0x3ef9bff8,
0xc0000000,0x40000000,0xbfb5bfb5,0xbfb53fb5,0xbec83ffb,0x3f8ebfd5,0xbfd53f8e,0x3ec83ffb,0x3fed3f44,0xbf44bfed,0x3f443fed,0x3fed3f44,
0x3f8ebfd5,0xbffbbec8,0x3ffbbec8,0x3fd5bf8e,0xbfedbf44,0x3fed3f44,0xbec8bffb,0xbffb3ec8,0xbf983fce,0x3fdcbf84,0xc000bdc9,0xbf5b3fe7,
0x3fa23fc6,0x3e49bfff,0xbf153ff5,0x3f713fe2,0x3fe7bf5b,0xbfbebfac,0x3fdc3f84,0x3ffd3e96,0xbfb5bfb5,0x3fb53fb5,0x3f44bfed,0xbfedbf44,
0xbfe23f71,0x3fffbe49,0xbfc6bfa2,0xbfe23f71,0x3ec83ffb,0x3f8ebfd5,0xbfd53f8e,0xbec83ffb,0x3fff3e49,0xbf15bff5,0x3f153ff5,0x3fa23fc6,
0xbf44bfed,0x3f443fed,0x3fd5bf8e,0xbf8ebfd5,0xc0003dc9,0x3ff13f2c,0xbef9bff8,0xbffdbe96,0xbf153ff5,0x3fe2bf71,0xbfffbe49,0xbfc63fa2,
0x3fce3f98,0x3ef9bff8,0xbf5b3fe7,0xbdc94000,0x4000,0x4000,0x4000,0xc0000000,0x40000000,0x3fed3f44,0x40000000,0xbf443fed,
0xc000,0x3fb5bfb5,0xc000,0x3fb53fb5,0xc0000000,0xbf44bfed,0xc0000000,0x3fedbf44,0xbfb53fb5,0xbfb53fb5,0xbfd53f8e,0xbf8ebfd5,
0x3fac3fbe,0x3f2c3ff1,0x3f843fdc,0xbffd3e96,0x3fc6bfa2,0x3fff3e49,0x3fe2bf71,0xbf153ff5,0xbf98bfce,0x3f84bfdc,0xbf5bbfe7,0x3fbe3fac,
0xc0000000,0xc0000000,0xbfedbf44,0x3f44bfed,0xbe493fff,0xbf713fe2,0xbf713fe2,0xbfa2bfc6,0x3ffb3ec8,0x3f8e3fd5,0x3fd53f8e,0xbffb3ec8,
0x3f15bff5,0x3fffbe49,0x3fa2bfc6,0xbf153ff5,0xbfb5bfb5,0xbfb5bfb5,0xbec8bffb,0x3ffbbec8,0xbfce3f98,0xbff83ef9,0xc0003dc9,0x3f2cbff1,
0x3f713fe2,0xbf153ff5,0xbe493fff,0xbfa2bfc6,0x3ff1bf2c,0x3fac3fbe,0x3ff83ef9,0xbffd3e96,0xc000,0xc000,0x3fb5bfb5,0x3fb53fb5,
0xbffbbec8,0xbfd5bf8e,0xbf8ebfd5,0x3ffbbec8,0xbf443fed,0xbfed3f44,0xbfed3f44,0x3f44bfed,0x3fd53f8e,0xbec83ffb,0x3ec83ffb,0xbf8ebfd5,
0x3fb5bfb5,0x3fb5bfb5,0x3ffb3ec8,0xbec83ffb,0xbf84bfdc,0xbe96bffd,0x3f5bbfe7,0x3fac3fbe,0xbff53f15,0xbfe2bf71,0xbfc6bfa2,0x3fffbe49,
0x3dc94000,0xbfe73f5b,0xbfce3f98,0x3f84bfdc,0x40000000,0x40000000,0x3f443fed,0xbfed3f44,0x3f15bff5,0x3fa2bfc6,0x3fffbe49,0xbf153ff5,
0xbfd5bf8e,0xbec8bffb,0x3ec8bffb,0x3f8e3fd5,0xbfc63fa2,0xbfe2bf71,0xbfe2bf71,0x3fff3e49,0x3fb53fb5,0x3fb53fb5,0xbf8e3fd5,0xbfd5bf8e,
0x3fe7bf5b,0x4000bdc9,0x3f983fce,0xbff83ef9,0xbe49bfff,0x3fa2bfc6,0x3ff5bf15,0xbf713fe2,0xbff8bef9,0xbe96bffd,0x3dc9c000,0x3f2c3ff1,
0x4000,0xc000,0x4000,0x40000000,0x40000000,0xbfedbf44,0x40000000,0x3f44bfed,0xc000,0xbfb53fb5,0xc000,0xbfb5bfb5,
0xc0000000,0x3f443fed,0xc0000000,0xbfed3f44,0xbfed3f44,0x3fedbf44,0xbffb3ec8,0x3ec83ffb,0x3f2c3ff1,0x3dc9c000,0x3e963ffd,0x3ff83ef9,
0x3ff5bf15,0xbfe2bf71,0x3fffbe49,0x3fa2bfc6,0xbef9bff8,0xbfce3f98,0xbdc9c000,0xbf5bbfe7,0xbfb5bfb5,0x3fb53fb5,0xbf44bfed,0xbfed3f44,
0xbfc63fa2,0x3ff5bf15,0xbff53f15,0xbe493fff,0x3f8e3fd5,0x3ec8bffb,0x3ec83ffb,0x3fd53f8e,0x3fe2bf71,0xbfc6bfa2,0x3fffbe49,0x3fe2bf71,
0x3f44bfed,0xbf443fed,0x3fd5bf8e,0xbf8ebfd5,0xbfdcbf84,0x3f983fce,0xbf5bbfe7,0xc0003dc9,0xbfa23fc6,0x3fffbe49,0xbff53f15,0xbf713fe2,
0x3fac3fbe,0x3f5bbfe7,0x3e963ffd,0x3f843fdc,0x40000000,0xc0000000,0x3fb53fb5,0x3fb5bfb5,0x3ec8bffb,0xbf8e3fd5,0x3fd5bf8e,0xbec8bffb,
0xbfedbf44,0x3f443fed,0xbf44bfed,0xbfedbf44,0xbf8e3fd5,0x3ffb3ec8,0xbffb3ec8,0xbfd53f8e,0x3f443fed,0xbf44bfed,0xbf8e3fd5,0x3fd53f8e,
0x3ffdbe96,0xbff8bef9,0x3fac3fbe,0x3ff1bf2c,0x3e49bfff,0xbfc63fa2,0x3fe2bf71,0x3f15bff5,0xbff1bf2c,0x3dc94000,0xbef9bff8,0xbf98bfce,
0xbfb53fb5,0x3fb5bfb5,0xbfedbf44,0xbf443fed,0x3f713fe2,0xbe49bfff,0xbfa23fc6,0x3f713fe2,0x3ffbbec8,0xbfd5bf8e,0x3f8e3fd5,0x3ffb3ec8,
0x3e49bfff,0xbff53f15,0x3ff5bf15,0x3fc6bfa2,0xbfedbf44,0x3fed3f44,0x3ec8bffb,0xbffbbec8,0xbfac3fbe,0x3fe7bf5b,0xbfdcbf84,0xbfce3f98,
0x3f713fe2,0x3f15bff5,0xbfc63fa2,0xbe493fff,0x3ffdbe96,0xbf84bfdc,0x3f2c3ff1,0x3fac3fbe,0x4000,0x4000,0x4000,0xc0000000,
0x40000000,0x3fed3f44,0x40000000,0xbf443fed,0xc000,0x3fb5bfb5,0xc000,0x3fb53fb5,0xc0000000,0xbf44bfed,0xc0000000,0x3fedbf44,
0xc0000000,0xc0000000,0xbffbbec8,0x3ec8bffb,0xbdc94000,0xbf5b3fe7,0xbef93ff8,0xbfcebf98,0x3fff3e49,0x3fa23fc6,0x3ff53f15,0xbfe23f71,
0x3e96bffd,0x3ff8bef9,0x3f2cbff1,0x3dc94000,0xc000,0xc000,0x3f44bfed,0x3fed3f44,0xbfffbe49,0xbfe2bf71,0xbfe2bf71,0x3fc6bfa2,
0xbec83ffb,0xbfd53f8e,0xbf8e3fd5,0xbec8bffb,0x3ff53f15,0x3e493fff,0x3fc63fa2,0xbff5bf15,0x40000000,0x40000000,0x3fd53f8e,0xbf8e3fd5,
0x3e96bffd,0x3f84bfdc,0x3facbfbe,0x3f5b3fe7,0xbff5bf15,0xbf71bfe2,0xbfa2bfc6,0x3fff3e49,0xbf5b3fe7,0xc000bdc9,0xbfdc3f84,0x3f98bfce,
0x4000,0x4000,0xbfb53fb5,0xbfb5bfb5,0x3ffb3ec8,0x3fd53f8e,0x3f8e3fd5,0xbffb3ec8,0x3f44bfed,0x3fedbf44,0x3fedbf44,0xbf443fed,
0xbfd5bf8e,0x3ec8bffb,0xbec8bffb,0x3f8e3fd5,0xc0000000,0xc0000000,0xbf8ebfd5,0x3fd5bf8e,0xbef93ff8,0xbf983fce,0xbff13f2c,0x3dc9c000,
0x3fe23f71,0x3f153ff5,0x3e493fff,0xbfc6bfa2,0x3facbfbe,0x3ff13f2c,0x3ffd3e96,0xbff83ef9,0xc000,0xc000,0x3fedbf44,0x3f443fed,
0xbff5bf15,0xbfc6bfa2,0xbe49bfff,0x3ff53f15,0xbf8e3fd5,0xbffb3ec8,0xbffbbec8,0x3fd5bf8e,0x3fa23fc6,0xbf713fe2,0xbf713fe2,0x3e49bfff,
0x40000000,0x40000000,0x3ec83ffb,0xbffb3ec8,0x3f2cbff1,0x3facbfbe,0x3ffd3e96,0xbf843fdc,0xbfc6bfa2,0xbe49bfff,0x3f71bfe2,0x3f153ff5,
0xbfdc3f84,0xbfcebf98,0xbfacbfbe,0x3fe73f5b,0x4000,0xc000,0x4000,0x40000000,0x40000000,0xbfedbf44,0x40000000,0x3f44bfed,
0xc000,0xbfb53fb5,0xc000,0xbfb5bfb5,0xc0000000,0x3f443fed,0xc0000000,0xbfed3f44,0xbfedbf44,0x3fed3f44,0xbfd5bf8e,0xbf8e3fd5,
0xbf5b3fe7,0x3fbebfac,0xbf983fce,0x3f843fdc,0x3fe23f71,0xbf15bff5,0x3fc63fa2,0x3fffbe49,0x3f84bfdc,0xbffdbe96,0x3facbfbe,0x3f2cbff1,
0x3fb5bfb5,0xbfb53fb5,0x3fedbf44,0xbf44bfed,0xbfa2bfc6,0x3f153ff5,0xbf15bff5,0xbfffbe49,0xbfd53f8e,0x3ffb3ec8,0xbffb3ec8,0xbf8e3fd5,
0x3f713fe2,0x3fa2bfc6,0x3e493fff,0x3f713fe2,0x3f443fed,0xbf44bfed,0xbec83ffb,0x3ffb3ec8,0x3ff8bef9,0xbffdbe96,0x3ff13f2c,0x3facbfbe,
0xbe49bfff,0xbfa23fc6,0x3f71bfe2,0xbf15bff5,0xc000bdc9,0x3f2c3ff1,0xbfcebf98,0xbff8bef9,0xc0000000,0x40000000,0xbfb5bfb5,0xbfb53fb5,
0xbec83ffb,0x3f8ebfd5,0xbfd53f8e,0x3ec83ffb,0x3fed3f44,0xbf44bfed,0x3f443fed,0x3fed3f44,0x3f8ebfd5,0xbffbbec8,0x3ffbbec8,0x3fd5bf8e,
0x3f44bfed,0xbf443fed,0x3ffbbec8,0xbec8bffb,0xbfcebf98,0x3f843fdc,0x3dc9c000,0xbfe7bf5b,0xbfc63fa2,0x3fff3e49,0xbff5bf15,0xbfe23f71,
0x3f5b3fe7,0x3facbfbe,0xbf843fdc,0xbe963ffd,0x3fb53fb5,0xbfb5bfb5,0xbf443fed,0x3fed3f44,0x3fe2bf71,0xbfff3e49,0x3fc63fa2,0x3fe2bf71,
0xbec8bffb,0xbf8e3fd5,0x3fd5bf8e,0x3ec8bffb,0xbfffbe49,0x3f153ff5,0xbf15bff5,0xbfa2bfc6,0xbfed3f44,0x3fedbf44,0xbf8ebfd5,0xbfd53f8e,
0x3dc94000,0x3f2cbff1,0xbff83ef9,0xbe963ffd,0x3ff53f15,0xbf71bfe2,0xbe493fff,0x3fa23fc6,0x3f98bfce,0xbff8bef9,0x3fe73f5b,0x40003dc9,
0x4000,0x4000,0x4000,0xc0000000,0x40000000,0x3fed3f44,0x40000000,0xbf443fed,0xc000,0x3fb5bfb5,0xc000,0x3fb53fb5,
0xc0000000,0xbf44bfed,0xc0000000,0x3fedbf44,0xbfb5bfb5,0xbfb5bfb5,0xbf8ebfd5,0x3fd5bf8e,0xbfbe3fac,0xbff13f2c,0xbfdc3f84,0xbe96bffd,
0x3fa23fc6,0xbe493fff,0x3f713fe2,0xbff5bf15,0x3fcebf98,0x3fdc3f84,0x3fe7bf5b,0xbfac3fbe,0x40000000,0x40000000,0x3fed3f44,0xbf443fed,
0x3e49bfff,0x3f71bfe2,0x3f71bfe2,0x3fa23fc6,0xbffbbec8,0xbf8ebfd5,0xbfd5bf8e,0x3ffbbec8,0xbf153ff5,0xbfff3e49,0xbfa23fc6,0x3f15bff5,
0xbfb53fb5,0xbfb53fb5,0xbffb3ec8,0xbec8bffb,0x3f983fce,0x3ef93ff8,0x3dc94000,0xbff1bf2c,0x3fe2bf71,0x3ff53f15,0x3fff3e49,0xbfc63fa2,
0xbf2cbff1,0x3fbebfac,0x3ef9bff8,0x3e963ffd,0xc000,0xc000,0x3fb5bfb5,0x3fb53fb5,0xbffbbec8,0xbfd5bf8e,0xbf8ebfd5,0x3ffbbec8,
0xbf443fed,0xbfed3f44,0xbfed3f44,0x3f44bfed,0x3fd53f8e,0xbec83ffb,0x3ec83ffb,0xbf8ebfd5,0x3fb53fb5,0x3fb53fb5,0xbec83ffb,0xbffbbec8,
0x3fdcbf84,0x3ffdbe96,0x3fe73f5b,0xbfbe3fac,0xbf15bff5,0x3f71bfe2,0x3fa2bfc6,0x3e493fff,0xc0003dc9,0xbf5bbfe7,0xbf98bfce,0x3fdc3f84,
0xc0000000,0xc0000000,0xbf44bfed,0x3fedbf44,0xbf153ff5,0xbfa23fc6,0xbfff3e49,0x3f15bff5,0x3fd53f8e,0x3ec83ffb,0xbec83ffb,0xbf8ebfd5,
0x3fc6bfa2,0x3fe23f71,0x3fe23f71,0xbfffbe49,0x3fb5bfb5,0x3fb5bfb5,0x3fd53f8e,0xbf8e3fd5,0xbf5bbfe7,0xbdc9c000,0x3fcebf98,0x3ef93ff8,
0xbfff3e49,0xbfc6bfa2,0xbf15bff5,0x3fe23f71,0xbef93ff8,0xbffd3e96,0xc000bdc9,0x3ff1bf2c,0x4000,0xc000,0x4000,0x40000000,
0x40000000,0xbfedbf44,0x40000000,0x3f44bfed,0xc000,0xbfb53fb5,0xc000,0xbfb5bfb5,0xc0000000,0x3f443fed,0xc0000000,0xbfed3f44,
0xbf44bfed,0x3f443fed,0xbec8bffb,0xbffb3ec8,0xbff13f2c,0x40003dc9,0xbffd3e96,0xbef93ff8,0x3f153ff5,0x3f71bfe2,0x3e493fff,0x3fc63fa2,
0x3ff8bef9,0xbf98bfce,0x4000bdc9,0x3fe7bf5b,0x3fb53fb5,0xbfb5bfb5,0x3f443fed,0x3fedbf44,0x3fc6bfa2,0xbff53f15,0x3ff5bf15,0x3e49bfff,
0xbf8ebfd5,0xbec83ffb,0xbec8bffb,0xbfd5bf8e,0xbfe23f71,0x3fc63fa2,0xbfff3e49,0xbfe23f71,0xbfedbf44,0x3fed3f44,0xbf8ebfd5,0xbfd53f8e,
0xbf843fdc,0x3fcebf98,0xbfe73f5b,0x3dc94000,0x3fc63fa2,0xbe49bfff,0x3f153ff5,0x3fe23f71,0x3fbebfac,0xbfe7bf5b,0x3ffdbe96,0x3fdcbf84,
0x40000000,0xc0000000,0x3fb53fb5,0x3fb5bfb5,0x3ec8bffb,0xbf8e3fd5,0x3fd5bf8e,0xbec8bffb,0xbfedbf44,0x3f443fed,0xbf44bfed,0xbfedbf44,
0xbf8e3fd5,0x3ffb3ec8,0xbffb3ec8,0xbfd53f8e,0xbfed3f44,0x3fedbf44,0xbfd5bf8e,0xbf8e3fd5,0x3e963ffd,0x3ef9bff8,0xbfbe3fac,0x3f2c3ff1,
0x3fff3e49,0xbfa2bfc6,0x3f713fe2,0x3ff53f15,0x3f2cbff1,0xc0003dc9,0x3ff8bef9,0x3fcebf98,0x3fb5bfb5,0xbfb53fb5,0x3fed3f44,0x3f44bfed,
0xbf71bfe2,0x3e493fff,0x3fa2bfc6,0xbf71bfe2,0xbffb3ec8,0x3fd53f8e,0xbf8ebfd5,0xbffbbec8,0xbe493fff,0x3ff5bf15,0xbff53f15,0xbfc63fa2,
0xbf443fed,0x3f44bfed,0xbffbbec8,0xbec83ffb,0x3fbe3fac,0xbf5bbfe7,0xbf843fdc,0x3f983fce,0x3fe2bf71,0xbff5bf15,0x3fa23fc6,0x3fff3e49,
0xbe96bffd,0xbfdc3f84,0x3ff1bf2c,0x3fbebfac,0x3f803f80,0x3f803f80,0xc000,0x40000000,0x3fb53fb5,0x3f443fed,0xbfb5bfb5,0x3fedbf44,
0x40000000,0x3fb53fb5,0xc0000000,0x3fb5bfb5,0x3fb5bfb5,0x3fed3f44,0xbfb53fb5,0x3f44bfed,0xbf803f80,0xbf803f80,0x3ec8bffb,0x3ffb3ec8,
0x3fac3fbe,0x3f2c3ff1,0xbf84bfdc,0x3ffdbe96,0x3fff3e49,0x3fa23fc6,0xbff5bf15,0x3fe2bf71,0x3fcebf98,0x3fdc3f84,0xbfe73f5b,0x3facbfbe,
0x3f803f80,0x3f803f80,0x3f44bfed,0x3fed3f44,0x3fa23fc6,0x3f153ff5,0xbf15bff5,0x3fff3e49,0x3ffb3ec8,0x3f8e3fd5,0xbfd5bf8e,0x3ffbbec8,
0x3fe2bf71,0x3fc63fa2,0xbfff3e49,0x3fe2bf71,0xbf803f80,0xbf803f80,0x3f8ebfd5,0x3fd53f8e,0x3f983fce,0x3ef93ff8,0xbdc9c000,0x3ff13f2c,
0x3ff53f15,0x3f713fe2,0xbfa2bfc6,0x3fff3e49,0x3ff1bf2c,0x3fac3fbe,0xbff8bef9,0x3ffdbe96,0x3f803f80,0x3f803f80,0x3fb5bfb5,0x3fb53fb5,
0x3f8e3fd5,0x3ec83ffb,0x3ec8bffb,0x3fd53f8e,0x3fed3f44,0x3f443fed,0xbf44bfed,0x3fed3f44,0x3ffbbec8,0x3f8e3fd5,0xbfd5bf8e,0x3ffb3ec8,
0xbf803f80,0xbf803f80,0x3fd5bf8e,0x3f8e3fd5,0x3f843fdc,0x3e963ffd,0x3f5bbfe7,0x3fac3fbe,0x3fe23f71,0x3f153ff5,0xbe49bfff,0x3fc63fa2,
0x4000bdc9,0x3f5b3fe7,0xbf98bfce,0x3fdc3f84,0x3f803f80,0x3f803f80,0x3fedbf44,0x3f443fed,0x3f713fe2,0x3e493fff,0x3fa2bfc6,0x3f713fe2,
0x3fd53f8e,0x3ec83ffb,0x3ec8bffb,0x3f8e3fd5,0x3fff3e49,0x3f153ff5,0xbf15bff5,0x3fa23fc6,0xbf803f80,0xbf803f80,0x3ffbbec8,0x3ec83ffb,
0x3f5b3fe7,0x3dc94000,0x3fcebf98,0x3ef93ff8,0x3fc63fa2,0x3e493fff,0x3f71bfe2,0x3f153ff5,0x3ff83ef9,0x3e963ffd,0x3dc9c000,0x3f2c3ff1,
0x4000,0xc000,0xc000,0xc0000000,0x3fb53fb5,0xbf44bfed,0xbfb5bfb5,0xbfed3f44,0x40000000,0xbfb5bfb5,0xc0000000,0xbfb53fb5,
0x3fb5bfb5,0xbfedbf44,0xbfb53fb5,0xbf443fed,0xbf443fed,0x3f44bfed,0x3f8ebfd5,0xbfd5bf8e,0x3f2c3ff1,0x3dc9c000,0xbe96bffd,0xbff8bef9,
0x3fe23f71,0xbf15bff5,0xbfc6bfa2,0xbfff3e49,0x3ff8bef9,0xbf98bfce,0xc0003dc9,0xbfe73f5b,0xbfb53fb5,0x3fb5bfb5,0x3fedbf44,0xbf44bfed,
0xbe493fff,0x3f71bfe2,0x3f71bfe2,0xbfa2bfc6,0x3f8e3fd5,0x3ec8bffb,0xbec8bffb,0xbfd5bf8e,0x3ff53f15,0xbe49bfff,0xbfc6bfa2,0xbff5bf15,
0xbfed3f44,0x3fedbf44,0x3ffb3ec8,0x3ec8bffb,0xbf843fdc,0x3fcebf98,0x3fe7bf5b,0xbdc9c000,0x3e493fff,0x3fa2bfc6,0x3f71bfe2,0xbf15bff5,
0x3fac3fbe,0x3f5bbfe7,0xbe96bffd,0xbf84bfdc,0xc0000000,0x40000000,0x3fb53fb5,0x3fb5bfb5,0xbfd53f8e,0x3ffbbec8,0x3ffb3ec8,0x3f8ebfd5,
0xbf443fed,0x3fedbf44,0x3fedbf44,0x3f44bfed,0x3ec83ffb,0x3fd5bf8e,0x3f8ebfd5,0x3ec8bffb,0xbfedbf44,0x3fed3f44,0x3ec83ffb,0x3ffbbec8,
0xbffd3e96,0x3ff83ef9,0x3fac3fbe,0x3ff1bf2c,0xbfc63fa2,0x3fff3e49,0x3ff53f15,0x3fe2bf71,0xbf2c3ff1,0x4000bdc9,0x3ff8bef9,0x3fcebf98,
0xbfb5bfb5,0x3fb53fb5,0xbf443fed,0x3fed3f44,0xbff5bf15,0x3fc63fa2,0x3e493fff,0x3ff53f15,0xbffb3ec8,0x3fd53f8e,0x3f8e3fd5,0x3ffb3ec8,
0xbfc63fa2,0x3fe23f71,0x3fe23f71,0x3fff3e49,0xbf44bfed,0x3f443fed,0xbfd53f8e,0x3f8e3fd5,0xbfbebfac,0x3f5b3fe7,0xbf843fdc,0x3f983fce,
0xbff5bf15,0x3f713fe2,0xbe493fff,0x3fa23fc6,0xbffd3e96,0x3f843fdc,0x3f2c3ff1,0x3fac3fbe,0x4000,0x4000,0xc000,0x40000000,
0x3fb53fb5,0x3f443fed,0xbfb5bfb5,0x3fedbf44,0x40000000,0x3fb53fb5,0xc0000000,0x3fb5bfb5,0x3fb5bfb5,0x3fed3f44,0xbfb53fb5,0x3f44bfed,
0xbfb53fb5,0xbfb53fb5,0x3fd5bf8e,0x3f8e3fd5,0xbdc94000,0xbf5b3fe7,0x3ef9bff8,0x3fce3f98,0x3fa23fc6,0xbe493fff,0xbf71bfe2,0x3ff53f15,
0x3ffd3e96,0x3ef93ff8,0xbff1bf2c,0x4000bdc9,0xc0000000,0xc0000000,0x3fed3f44,0xbf443fed,0xbfc63fa2,0xbff53f15,0x3ff5bf15,0xbe493fff,
0xbec83ffb,0xbfd53f8e,0x3f8ebfd5,0x3ec83ffb,0x3f713fe2,0xbfa23fc6,0xbe49bfff,0x3f713fe2,0xbfb5bfb5,0xbfb5bfb5,0x3ec83ffb,0xbffb3ec8,
0xbffdbe96,0xbfdcbf84,0x3fbe3fac,0xbfe73f5b,0xbfe23f71,0xbff5bf15,0x3fff3e49,0xbfc63fa2,0xbf5b3fe7,0xc000bdc9,0x3fdcbf84,0xbf983fce,
0xc000,0xc000,0xbfb53fb5,0xbfb5bfb5,0xbf8ebfd5,0xbec8bffb,0xbec83ffb,0xbfd5bf8e,0xbfedbf44,0xbf44bfed,0x3f443fed,0xbfedbf44,
0xbffb3ec8,0xbf8ebfd5,0x3fd53f8e,0xbffbbec8,0x3fb5bfb5,0x3fb5bfb5,0xbffbbec8,0x3ec8bffb,0x3ef9bff8,0x3f98bfce,0xbff13f2c,0x3dc9c000,
0xbf15bff5,0x3f71bfe2,0xbfa23fc6,0xbe49bfff,0xbfbebfac,0x3f2cbff1,0xbe963ffd,0xbef9bff8,0x40000000,0x40000000,0xbf44bfed,0x3fedbf44,
0x3fe2bf71,0x3fffbe49,0xbfc6bfa2,0x3fe2bf71,0x3f8ebfd5,0x3ffbbec8,0xbffbbec8,0x3fd5bf8e,0x3e49bfff,0x3ff5bf15,0xbff53f15,0x3fc6bfa2,
0x3fb53fb5,0x3fb53fb5,0x3f8ebfd5,0x3fd53f8e,0x3ff13f2c,0x3fbe3fac,0x3e96bffd,0x3fdc3f84,0x3fffbe49,0x3fc63fa2,0xbf15bff5,0x3fe23f71,
0x3fdcbf84,0x3fce3f98,0xbfacbfbe,0x3fe73f5b,0x4000,0xc000,0xc000,0xc0000000,0x3fb53fb5,0xbf44bfed,0xbfb5bfb5,0xbfed3f44,
0x40000000,0xbfb5bfb5,0xc0000000,0xbfb53fb5,0x3fb5bfb5,0xbfedbf44,0xbfb53fb5,0xbf443fed,0xbfed3f44,0x3fedbf44,0x3ffbbec8,0xbec8bffb,
0xbf5b3fe7,0x3fbebfac,0x3f98bfce,0xbf84bfdc,0x3f153ff5,0x3f71bfe2,0xbe49bfff,0xbfc6bfa2,0x3fdc3f84,0x3e96bffd,0xbfbebfac,0xbff1bf2c,
0xbfb5bfb5,0x3fb53fb5,0x3f443fed,0x3fedbf44,0xbfffbe49,0x3fe23f71,0x3fe23f71,0x3fc6bfa2,0xbfd53f8e,0x3ffb3ec8,0x3ffbbec8,0x3f8ebfd5,
0xbf153ff5,0x3fffbe49,0x3fa2bfc6,0x3f15bff5,0x3f44bfed,0xbf443fed,0xbfd53f8e,0x3f8e3fd5,0xbef9bff8,0xbe963ffd,0xbf2c3ff1,0x3fbe3fac,
0xbfc6bfa2,0x3e493fff,0x3f153ff5,0x3fe23f71,0xc000bdc9,0x3f2c3ff1,0x3fce3f98,0x3ff83ef9,0x40000000,0xc0000000,0xbfb5bfb5,0xbfb53fb5,
0x3fd5bf8e,0xbffb3ec8,0xbffbbec8,0xbf8e3fd5,0x3f44bfed,0xbfed3f44,0xbfed3f44,0xbf443fed,0xbec8bffb,0xbfd53f8e,0xbf8e3fd5,0xbec83ffb,
0x3f443fed,0xbf44bfed,0x3f8ebfd5,0xbfd5bf8e,0x3fce3f98,0xbf84bfdc,0x3dc9c000,0xbfe7bf5b,0x3fff3e49,0xbfa2bfc6,0xbf71bfe2,0xbff5bf15,
0x3fe7bf5b,0xbfbebfac,0xbfdcbf84,0xbffdbe96,0xbfb53fb5,0x3fb5bfb5,0x3fed3f44,0x3f44bfed,0xbf153ff5,0x3fa2bfc6,0x3fffbe49,0x3f15bff5,
0x3ec83ffb,0x3f8ebfd5,0x3fd5bf8e,0x3ec8bffb,0x3fa23fc6,0x3f71bfe2,0x3f71bfe2,0x3e49bfff,0xbfedbf44,0x3fed3f44,0xbec83ffb,0x3ffb3ec8,
0xc0003dc9,0x3ff13f2c,0x3ef93ff8,0x3ffd3e96,0xbfe23f71,0x3ff53f15,0x3fa23fc6,0x3fff3e49,0xbf983fce,0x3ff83ef9,0x3fe73f5b,0x40003dc9,
0x4000,0x4000,0xc000,0x40000000,0x3fb53fb5,0x3f443fed,0xbfb5bfb5,0x3fedbf44,0x40000000,0x3fb53fb5,0xc0000000,0x3fb5bfb5,
0x3fb5bfb5,0x3fed3f44,0xbfb53fb5,0x3f44bfed,0xc0000000,0xc0000000,0x3ffb3ec8,0xbec83ffb,0xbfbe3fac,0xbff13f2c,0x3fdcbf84,0x3e963ffd,
0xbe493fff,0xbfc63fa2,0x3f15bff5,0x3f713fe2,0x3f983fce,0xbf843fdc,0xbf5bbfe7,0x3fbe3fac,0xc000,0xc000,0xbf443fed,0xbfedbf44,
0xbfa2bfc6,0xbf15bff5,0x3f153ff5,0xbfffbe49,0xbffbbec8,0xbf8ebfd5,0x3fd53f8e,0xbffb3ec8,0xbfe23f71,0xbfc6bfa2,0x3fffbe49,0xbfe23f71,
0x40000000,0x40000000,0xbfd5bf8e,0x3f8ebfd5,0x3fcebf98,0x3ff8bef9,0xc0003dc9,0x3f2cbff1,0x3f15bff5,0x3fe2bf71,0xbfc63fa2,0x3e49bfff,
0xbf2cbff1,0x3fbebfac,0xbef93ff8,0xbe96bffd,0x4000,0x4000,0x3fb5bfb5,0x3fb53fb5,0x3f8e3fd5,0x3ec83ffb,0x3ec8bffb,0x3fd53f8e,
0x3fed3f44,0x3f443fed,0xbf44bfed,0x3fed3f44,0x3ffbbec8,0x3f8e3fd5,0xbfd5bf8e,0x3ffb3ec8,0xc0000000,0xc0000000,0x3f8e3fd5,0xbfd53f8e,
0xbfdc3f84,0xbffd3e96,0x3fe73f5b,0xbfbe3fac,0xbf713fe2,0xbff53f15,0x3fffbe49,0xbfa23fc6,0x3dc94000,0xbfe73f5b,0x3fcebf98,0xbf843fdc,
0xc000,0xc000,0xbfed3f44,0xbf44bfed,0xbf71bfe2,0xbe49bfff,0xbfa23fc6,0xbf71bfe2,0xbfd5bf8e,0xbec8bffb,0xbec83ffb,0xbf8ebfd5,
0xbfffbe49,0xbf15bff5,0x3f153ff5,0xbfa2bfc6,0x40000000,0x40000000,0xbec8bffb,0x3ffbbec8,0x3fe7bf5b,0x4000bdc9,0xbf98bfce,0x3ff8bef9,
0x3fa2bfc6,0x3fffbe49,0xbfe2bf71,0x3ff5bf15,0x3ef9bff8,0x3ffdbe96,0xc000bdc9,0x3ff1bf2c,0x4000,0xc000,0xc000,0xc0000000,
0x3fb53fb5,0xbf44bfed,0xbfb5bfb5,0xbfed3f44,0x40000000,0xbfb5bfb5,0xc0000000,0xbfb53fb5,0x3fb5bfb5,0xbfedbf44,0xbfb53fb5,0xbf443fed,
0xbfedbf44,0x3fed3f44,0x3fd53f8e,0x3f8ebfd5,0xbff13f2c,0x40003dc9,0x3ffdbe96,0x3ef9bff8,0xbf713fe2,0x3ff5bf15,0x3fa2bfc6,0xbe49bfff,
0x3ef93ff8,0x3fcebf98,0xbdc9c000,0xbf5bbfe7,0x3fb5bfb5,0xbfb53fb5,0xbfed3f44,0x3f443fed,0x3e49bfff,0xbf713fe2,0xbf713fe2,0x3fa23fc6,
0xbf8ebfd5,0xbec83ffb,0x3ec83ffb,0x3fd53f8e,0xbff5bf15,0x3e493fff,0x3fc63fa2,0x3ff53f15,0x3f443fed,0xbf44bfed,0x3ec8bffb,0xbffbbec8,
0x3fdc3f84,0xbf98bfce,0xbf5bbfe7,0xc0003dc9,0x3fffbe49,0xbfc6bfa2,0xbfe2bf71,0xbff53f15,0x3fbebfac,0xbfe7bf5b,0xbffd3e96,0xbfdc3f84,
0xc0000000,0x40000000,0x3fb53fb5,0x3fb5bfb5,0xbfd53f8e,0x3ffbbec8,0x3ffb3ec8,0x3f8ebfd5,0xbf443fed,0x3fedbf44,0x3fedbf44,0x3f44bfed,
0x3ec83ffb,0x3fd5bf8e,0x3f8ebfd5,0x3ec8bffb,0x3f44bfed,0xbf443fed,0xbffb3ec8,0x3ec83ffb,0xbe96bffd,0xbef93ff8,0xbfbe3fac,0x3f2c3ff1,
0xbfa2bfc6,0xbe493fff,0xbf153ff5,0x3f713fe2,0xbff1bf2c,0x3dc94000,0x3ef93ff8,0x3f983fce,0x3fb53fb5,0xbfb5bfb5,0x3f44bfed,0xbfedbf44,
0x3ff53f15,0xbfc6bfa2,0xbe49bfff,0xbff5bf15,0x3ffbbec8,0xbfd5bf8e,0xbf8ebfd5,0xbffbbec8,0x3fc6bfa2,0xbfe2bf71,0xbfe2bf71,0xbfffbe49,
0xbfed3f44,0x3fedbf44,0x3f8e3fd5,0x3fd5bf8e,0xbfac3fbe,0x3fe7bf5b,0x3fdc3f84,0x3fcebf98,0xbf153ff5,0x3fe2bf71,0x3fff3e49,0x3fc6bfa2,
0x3e963ffd,0x3fdcbf84,0x3ff1bf2c,0x3fbebfac,0x4000,0x4000,0xc000,0x40000000,0x3fb53fb5,0x3f443fed,0xbfb5bfb5,0x3fedbf44,
0x40000000,0x3fb53fb5,0xc0000000,0x3fb5bfb5,0x3fb5bfb5,0x3fed3f44,0xbfb53fb5,0x3f44bfed,0xbfb5bfb5,0xbfb5bfb5,0x3f8e3fd5,0xbfd53f8e,
0xc000bdc9,0xbfe7bf5b,0x3ff83ef9,0xbf983fce,0xbfc63fa2,0xbfffbe49,0x3fe2bf71,0xbf153ff5,0xbe963ffd,0xbff83ef9,0x3f2cbff1,0x3dc94000,
0x40000000,0x40000000,0xbfedbf44,0x3f44bfed,0x3fc6bfa2,0x3ff5bf15,0xbff53f15,0x3e49bfff,0x3ec8bffb,0x3fd5bf8e,0xbf8e3fd5,0xbec8bffb,
0xbf71bfe2,0x3fa2bfc6,0x3e493fff,0xbf71bfe2,0xbfb53fb5,0xbfb53fb5,0x3ffbbec8,0x3ec83ffb,0xbe963ffd,0xbf843fdc,0x3facbfbe,0x3f5b3fe7,
0x3f713fe2,0xbf153ff5,0x3e49bfff,0x3fa23fc6,0x3fe73f5b,0xbdc94000,0xbf84bfdc,0x3fce3f98,0xc000,0xc000,0xbfb53fb5,0xbfb5bfb5,
0xbf8ebfd5,0xbec8bffb,0xbec83ffb,0xbfd5bf8e,0xbfedbf44,0xbf44bfed,0x3f443fed,0xbfedbf44,0xbffb3ec8,0xbf8ebfd5,0x3fd53f8e,0xbffbbec8,
0x3fb53fb5,0x3fb53fb5,0x3ec8bffb,0x3ffb3ec8,0x3ff83ef9,0x3fce3f98,0xbf2cbff1,0x40003dc9,0x3ff5bf15,0x3fe23f71,0xbfc6bfa2,0x3fffbe49,
0x3facbfbe,0x3ff13f2c,0xbffdbe96,0x3ff8bef9,0xc0000000,0xc0000000,0x3f443fed,0xbfed3f44,0xbfe23f71,0xbfff3e49,0x3fc63fa2,0xbfe23f71,
0xbf8e3fd5,0xbffb3ec8,0x3ffb3ec8,0xbfd53f8e,0xbe493fff,0xbff53f15,0x3ff5bf15,0xbfc63fa2,0x3fb5bfb5,0x3fb5bfb5,0xbfd5bf8e,0x3f8ebfd5,
0x3f2cbff1,0x3facbfbe,0xbffdbe96,0x3f84bfdc,0xbe49bfff,0x3fa2bfc6,0xbff53f15,0x3f71bfe2,0xbf84bfdc,0x3f98bfce,0xbfbe3fac,0x3f5bbfe7,
0x4000,0xc000,0xc000,0xc0000000,0x3fb53fb5,0xbf44bfed,0xbfb5bfb5,0xbfed3f44,0x40000000,0xbfb5bfb5,0xc0000000,0xbfb53fb5,
0x3fb5bfb5,0xbfedbf44,0xbfb53fb5,0xbf443fed,0xbf44bfed,0x3f443fed,0x3ec83ffb,0x3ffbbec8,0xbfe7bf5b,0x3fac3fbe,0x3fce3f98,0x3fdcbf84,
0xbff53f15,0x3fe23f71,0x3fffbe49,0x3fa2bfc6,0xbf843fdc,0x3ffd3e96,0x3facbfbe,0x3f2cbff1,0x3fb53fb5,0xbfb5bfb5,0xbf44bfed,0xbfed3f44,
0x3fff3e49,0xbfe2bf71,0xbfe2bf71,0xbfc63fa2,0x3fd5bf8e,0xbffbbec8,0xbffb3ec8,0xbf8e3fd5,0x3f15bff5,0xbfff3e49,0xbfa23fc6,0xbf153ff5,
0xbfedbf44,0x3fed3f44,0x3f8e3fd5,0x3fd5bf8e,0xbff83ef9,0x3ffd3e96,0x3ff13f2c,0x3facbfbe,0xbfa23fc6,0x3fffbe49,0x3ff5bf15,0x3f71bfe2,
0xbdc94000,0x3ff1bf2c,0x3f98bfce,0x3ef9bff8,0x40000000,0xc0000000,0xbfb5bfb5,0xbfb53fb5,0x3fd5bf8e,0xbffb3ec8,0xbffbbec8,0xbf8e3fd5,
0x3f44bfed,0xbfed3f44,0xbfed3f44,0xbf443fed,0xbec8bffb,0xbfd53f8e,0xbf8e3fd5,0xbec83ffb,0xbfed3f44,0x3fedbf44,0x3fd53f8e,0x3f8ebfd5,
0xbf983fce,0x3fdcbf84,0x40003dc9,0x3f5bbfe7,0xbe493fff,0x3fc6bfa2,0x3fe2bf71,0x3f15bff5,0x3f5b3fe7,0x3facbfbe,0x3f84bfdc,0x3e96bffd,
0x3fb5bfb5,0xbfb53fb5,0xbfedbf44,0xbf443fed,0x3f15bff5,0xbfa23fc6,0xbfff3e49,0xbf153ff5,0xbec8bffb,0xbf8e3fd5,0xbfd53f8e,0xbec83ffb,
0xbfa2bfc6,0xbf713fe2,0xbf713fe2,0xbe493fff,0xbf443fed,0x3f44bfed,0x3ffb3ec8,0x3ec8bffb,0x3dc94000,0x3f2cbff1,0x3ff8bef9,0x3e96bffd,
0x3f713fe2,0x3f15bff5,0x3fc6bfa2,0x3e49bfff,0x3fce3f98,0x3ef9bff8,0x3f5bbfe7,0x3dc9c000,
};
alignas(128) __device__ const uint32_t T_FFT[3328] = {
0x3f803f80,0x3f803f80,0x3f803f80,0x3f803f80,0x3f803f80,0x3f803f80,0x3f803f80,0x3f803f80,0x3f803f80,0x3f803f80,0x3f803f80,0x3f803f80,
0x3f803f80,0x3f803f80,0x3f803f80,0x3f803f80,0xbf803f80,0xbf353f35,0,0x3f35bf35,0xbf803f80,0xbf353f35,0,0x3f35bf35,
0xbf803f80,0xbf353f35,0,0x3f35bf35,0xbf803f80,0xbf353f35,0,0x3f35bf35,0xbf350000,0xbf55be48,0xbf6dbec4,0xbf7bbf0e,
0x3f353f80,0x3f0e3f7b,0x3ec43f6d,0x3e483f55,0x3f350000,0x3f553e48,0x3f6d3ec4,0x3f7b3f0e,0xbf35bf80,0xbf0ebf7b,0xbec4bf6d,0xbe48bf55,
0x3f350000,0x3f7bbf55,0x3ec4bf6d,0xbf0ebe48,0xbf353f80,0x3e483f0e,0x3f6dbec4,0x3f55bf7b,0xbf350000,0xbf7b3f55,0xbec43f6d,0x3f0e3e48,
0x3f35bf80,0xbe48bf0e,0xbf6d3ec4,0xbf553f7b,0x3f80,0xbec43f6d,0xbf353f35,0xbf6d3ec4,0xbf80,0x3ec4bf6d,0x3f35bf35,0x3f6dbec4,
0x3f80,0xbec43f6d,0xbf353f35,0xbf6d3ec4,0xbf80,0x3ec4bf6d,0x3f35bf35,0x3f6dbec4,0x3f80,0x3f6d3ec4,0x3f35bf35,0xbec4bf6d,
0xbf80,0xbf6dbec4,0xbf353f35,0x3ec43f6d,0x3f80,0x3f6d3ec4,0x3f35bf35,0xbec4bf6d,0xbf80,0xbf6dbec4,0xbf353f35,0x3ec43f6d,
0xbf350000,0xbe48bf0e,0x3ec4bf6d,0x3f55bf7b,0x3f35bf80,0x3f7bbf55,0x3f6dbec4,0x3f0e3e48,0x3f350000,0x3e483f0e,0xbec43f6d,0xbf553f7b,
0xbf353f80,0xbf7b3f55,0xbf6d3ec4,0xbf0ebe48,0x3f350000,0xbf0ebf7b,0xbf6dbec4,0x3e483f55,0xbf35bf80,0xbf55be48,0x3ec43f6d,0x3f7b3f0e,
0xbf350000,0x3f0e3f7b,0x3f6d3ec4,0xbe48bf55,0x3f353f80,0x3f553e48,0xbec4bf6d,0xbf7bbf0e,0x3f803f80,0,0xbf80bf80,0,
0x3f803f80,0,0xbf80bf80,0,0x3f803f80,0,0xbf80bf80,0,0x3f803f80,0,0xbf80bf80,0,
0xbf803f80,0x3f35bf35,0,0xbf353f35,0xbf803f80,0x3f35bf35,0,0xbf353f35,0xbf803f80,0x3f35bf35,0,0xbf353f35,
0xbf803f80,0x3f35bf35,0,0xbf353f35,0xbf350000,0xbf0ebf7b,0x3f6d3ec4,0x3e483f55,0x3f353f80,0xbf55be48,0xbec4bf6d,0x3f7b3f0e,
0x3f350000,0x3f0e3f7b,0xbf6dbec4,0xbe48bf55,0xbf35bf80,0x3f553e48,0x3ec43f6d,0xbf7bbf0e,0x3f350000,0xbe48bf0e,0xbec43f6d,0x3f55bf7b,
0xbf353f80,0x3f7bbf55,0xbf6d3ec4,0x3f0e3e48,0xbf350000,0x3e483f0e,0x3ec4bf6d,0xbf553f7b,0x3f35bf80,0xbf7b3f55,0x3f6dbec4,0xbf0ebe48,
0x3f80,0xbf6dbec4,0x3f35bf35,0x3ec43f6d,0xbf80,0x3f6d3ec4,0xbf353f35,0xbec4bf6d,0x3f80,0xbf6dbec4,0x3f35bf35,0x3ec43f6d,
0xbf80,0x3f6d3ec4,0xbf353f35,0xbec4bf6d,0x3f80,0x3ec4bf6d,0xbf353f35,0x3f6dbec4,0xbf80,0xbec43f6d,0x3f35bf35,0xbf6d3ec4,
0x3f80,0x3ec4bf6d,0xbf353f35,0x3f6dbec4,0xbf80,0xbec43f6d,0x3f35bf35,0xbf6d3ec4,0xbf350000,0x3f7bbf55,0xbec43f6d,0xbf0ebe48,
0x3f35bf80,0x3e483f0e,0xbf6d3ec4,0x3f55bf7b,0x3f350000,0xbf7b3f55,0x3ec4bf6d,0x3f0e3e48,0xbf353f80,0xbe48bf0e,0x3f6dbec4,0xbf553f7b,
0x3f350000,0xbf55be48,0x3f6d3ec4,0xbf7bbf0e,0xbf35bf80,0x3f0e3f7b,0xbec4bf6d,0x3e483f55,0xbf350000,0x3f553e48,0xbf6dbec4,0x3f7b3f0e,
0x3f353f80,0xbf0ebf7b,0x3ec43f6d,0xbe48bf55,0x3f803f80,0xbf80bf80,0x3f803f80,0xbf80bf80,0x3f803f80,0xbf80bf80,0x3f803f80,0xbf80bf80,
0x3f803f80,0xbf80bf80,0x3f803f80,0xbf80bf80,0x3f803f80,0xbf80bf80,0x3f803f80,0xbf80bf80,0xbf803f80,0x3f35bf35,0,0xbf353f35,
0xbf803f80,0x3f35bf35,0,0xbf353f35,0xbf803f80,0x3f35bf35,0,0xbf353f35,0xbf803f80,0x3f35bf35,0,0xbf353f35,
0xbf350000,0x3f553e48,0xbf6dbec4,0x3f7b3f0e,0x3f353f80,0xbf0ebf7b,0x3ec43f6d,0xbe48bf55,0x3f350000,0xbf55be48,0x3f6d3ec4,0xbf7bbf0e,
0xbf35bf80,0x3f0e3f7b,0xbec4bf6d,0x3e483f55,0x3f350000,0xbf7b3f55,0x3ec4bf6d,0x3f0e3e48,0xbf353f80,0xbe48bf0e,0x3f6dbec4,0xbf553f7b,
0xbf350000,0x3f7bbf55,0xbec43f6d,0xbf0ebe48,0x3f35bf80,0x3e483f0e,0xbf6d3ec4,0x3f55bf7b,0x3f80,0x3ec4bf6d,0xbf353f35,0x3f6dbec4,
0xbf80,0xbec43f6d,0x3f35bf35,0xbf6d3ec4,0x3f80,0x3ec4bf6d,0xbf353f35,0x3f6dbec4,0xbf80,0xbec43f6d,0x3f35bf35,0xbf6d3ec4,
0x3f80,0xbf6dbec4,0x3f35bf35,0x3ec43f6d,0xbf80,0x3f6d3ec4,0xbf353f35,0xbec4bf6d,0x3f80,0xbf6dbec4,0x3f35bf35,0x3ec43f6d,
0xbf80,0x3f6d3ec4,0xbf353f35,0xbec4bf6d,0xbf350000,0x3e483f0e,0x3ec4bf6d,0xbf553f7b,0x3f35bf80,0xbf7b3f55,0x3f6dbec4,0xbf0ebe48,
0x3f350000,0xbe48bf0e,0xbec43f6d,0x3f55bf7b,0xbf353f80,0x3f7bbf55,0xbf6d3ec4,0x3f0e3e48,0x3f350000,0x3f0e3f7b,0xbf6dbec4,0xbe48bf55,
0xbf35bf80,0x3f553e48,0x3ec43f6d,0xbf7bbf0e,0xbf350000,0xbf0ebf7b,0x3f6d3ec4,0x3e483f55,0x3f353f80,0xbf55be48,0xbec4bf6d,0x3f7b3f0e,
0x3f803f80,0,0xbf80bf80,0,0x3f803f80,0,0xbf80bf80,0,0x3f803f80,0,0xbf80bf80,0,
0x3f803f80,0,0xbf80bf80,0,0xbf803f80,0xbf353f35,0,0x3f35bf35,0xbf803f80,0xbf353f35,0,0x3f35bf35,
0xbf803f80,0xbf353f35,0,0x3f35bf35,0xbf803f80,0xbf353f35,0,0x3f35bf35,0xbf350000,0x3f0e3f7b,0x3f6d3ec4,0xbe48bf55,
0x3f353f80,0x3f553e48,0xbec4bf6d,0xbf7bbf0e,0x3f350000,0xbf0ebf7b,0xbf6dbec4,0x3e483f55,0xbf35bf80,0xbf55be48,0x3ec43f6d,0x3f7b3f0e,
0x3f350000,0x3e483f0e,0xbec43f6d,0xbf553f7b,0xbf353f80,0xbf7b3f55,0xbf6d3ec4,0xbf0ebe48,0xbf350000,0xbe48bf0e,0x3ec4bf6d,0x3f55bf7b,
0x3f35bf80,0x3f7bbf55,0x3f6dbec4,0x3f0e3e48,0x3f80,0x3f6d3ec4,0x3f35bf35,0xbec4bf6d,0xbf80,0xbf6dbec4,0xbf353f35,0x3ec43f6d,
0x3f80,0x3f6d3ec4,0x3f35bf35,0xbec4bf6d,0xbf80,0xbf6dbec4,0xbf353f35,0x3ec43f6d,0x3f80,0xbec43f6d,0xbf353f35,0xbf6d3ec4,
0xbf80,0x3ec4bf6d,0x3f35bf35,0x3f6dbec4,0x3f80,0xbec43f6d,0xbf353f35,0xbf6d3ec4,0xbf80,0x3ec4bf6d,0x3f35bf35,0x3f6dbec4,
0xbf350000,0xbf7b3f55,0xbec43f6d,0x3f0e3e48,0x3f35bf80,0xbe48bf0e,0xbf6d3ec4,0xbf553f7b,0x3f350000,0x3f7bbf55,0x3ec4bf6d,0xbf0ebe48,
0xbf353f80,0x3e483f0e,0x3f6dbec4,0x3f55bf7b,0x3f350000,0x3f553e48,0x3f6d3ec4,0x3f7b3f0e,0xbf35bf80,0xbf0ebf7b,0xbec4bf6d,0xbe48bf55,
0xbf350000,0xbf55be48,0xbf6dbec4,0xbf7bbf0e,0x3f353f80,0x3f0e3f7b,0x3ec43f6d,0x3e483f55,0,0,0,0,
0,0,0,0,0,0,0,0,0,0,0,0,
0,0x3f35bf35,0x3f80bf80,0x3f35bf35,0,0x3f35bf35,0x3f80bf80,0x3f35bf35,0,0x3f35bf35,0x3f80bf80,0x3f35bf35,
0,0x3f35bf35,0x3f80bf80,0x3f35bf35,0xbf35bf80,0xbf0ebf7b,0xbec4bf6d,0xbe48bf55,0xbf350000,0xbf55be48,0xbf6dbec4,0xbf7bbf0e,
0x3f353f80,0x3f0e3f7b,0x3ec43f6d,0x3e483f55,0x3f350000,0x3f553e48,0x3f6d3ec4,0x3f7b3f0e,0x3f35bf80,0xbe48bf0e,0xbf6d3ec4,0xbf553f7b,
0x3f350000,0x3f7bbf55,0x3ec4bf6d,0xbf0ebe48,0xbf353f80,0x3e483f0e,0x3f6dbec4,0x3f55bf7b,0xbf350000,0xbf7b3f55,0xbec43f6d,0x3f0e3e48,
0xbf800000,0xbf6dbec4,0xbf35bf35,0xbec4bf6d,0x3f800000,0x3f6d3ec4,0x3f353f35,0x3ec43f6d,0xbf800000,0xbf6dbec4,0xbf35bf35,0xbec4bf6d,
0x3f800000,0x3f6d3ec4,0x3f353f35,0x3ec43f6d,0x3f800000,0x3ec4bf6d,0xbf35bf35,0xbf6d3ec4,0xbf800000,0xbec43f6d,0x3f353f35,0x3f6dbec4,
0x3f800000,0x3ec4bf6d,0xbf35bf35,0xbf6d3ec4,0xbf800000,0xbec43f6d,0x3f353f35,0x3f6dbec4,0x3f35bf80,0x3f7bbf55,0x3f6dbec4,0x3f0e3e48,
0x3f350000,0x3e483f0e,0xbec43f6d,0xbf553f7b,0xbf353f80,0xbf7b3f55,0xbf6d3ec4,0xbf0ebe48,0xbf350000,0xbe48bf0e,0x3ec4bf6d,0x3f55bf7b,
0xbf35bf80,0xbf55be48,0x3ec43f6d,0x3f7b3f0e,0xbf350000,0x3f0e3f7b,0x3f6d3ec4,0xbe48bf55,0x3f353f80,0x3f553e48,0xbec4bf6d,0xbf7bbf0e,
0x3f350000,0xbf0ebf7b,0xbf6dbec4,0x3e483f55,0,0xbf80bf80,0,0x3f803f80,0,0xbf80bf80,0,0x3f803f80,
0,0xbf80bf80,0,0x3f803f80,0,0xbf80bf80,0,0x3f803f80,0,0x3f35bf35,0xbf803f80,0x3f35bf35,
0,0x3f35bf35,0xbf803f80,0x3f35bf35,0,0x3f35bf35,0xbf803f80,0x3f35bf35,0,0x3f35bf35,0xbf803f80,0x3f35bf35,
0xbf35bf80,0x3f553e48,0x3ec43f6d,0xbf7bbf0e,0xbf350000,0xbf0ebf7b,0x3f6d3ec4,0x3e483f55,0x3f353f80,0xbf55be48,0xbec4bf6d,0x3f7b3f0e,
0x3f350000,0x3f0e3f7b,0xbf6dbec4,0xbe48bf55,0x3f35bf80,0xbf7b3f55,0x3f6dbec4,0xbf0ebe48,0x3f350000,0xbe48bf0e,0xbec43f6d,0x3f55bf7b,
0xbf353f80,0x3f7bbf55,0xbf6d3ec4,0x3f0e3e48,0xbf350000,0x3e483f0e,0x3ec4bf6d,0xbf553f7b,0xbf800000,0x3ec4bf6d,0x3f353f35,0xbf6d3ec4,
0x3f800000,0xbec43f6d,0xbf35bf35,0x3f6dbec4,0xbf800000,0x3ec4bf6d,0x3f353f35,0xbf6d3ec4,0x3f800000,0xbec43f6d,0xbf35bf35,0x3f6dbec4,
0x3f800000,0xbf6dbec4,0x3f353f35,0xbec4bf6d,0xbf800000,0x3f6d3ec4,0xbf35bf35,0x3ec43f6d,0x3f800000,0xbf6dbec4,0x3f353f35,0xbec4bf6d,
0xbf800000,0x3f6d3ec4,0xbf35bf35,0x3ec43f6d,0x3f35bf80,0x3e483f0e,0xbf6d3ec4,0x3f55bf7b,0x3f350000,0xbf7b3f55,0x3ec4bf6d,0x3f0e3e48,
0xbf353f80,0xbe48bf0e,0x3f6dbec4,0xbf553f7b,0xbf350000,0x3f7bbf55,0xbec43f6d,0xbf0ebe48,0xbf35bf80,0x3f0e3f7b,0xbec4bf6d,0x3e483f55,
0xbf350000,0x3f553e48,0xbf6dbec4,0x3f7b3f0e,0x3f353f80,0xbf0ebf7b,0x3ec43f6d,0xbe48bf55,0x3f350000,0xbf55be48,0x3f6d3ec4,0xbf7bbf0e,
0,0,0,0,0,0,0,0,0,0,0,0,
0,0,0,0,0,0xbf353f35,0x3f80bf80,0xbf353f35,0,0xbf353f35,0x3f80bf80,0xbf353f35,
0,0xbf353f35,0x3f80bf80,0xbf353f35,0,0xbf353f35,0x3f80bf80,0xbf353f35,0xbf35bf80,0x3f0e3f7b,0xbec4bf6d,0x3e483f55,
0xbf350000,0x3f553e48,0xbf6dbec4,0x3f7b3f0e,0x3f353f80,0xbf0ebf7b,0x3ec43f6d,0xbe48bf55,0x3f350000,0xbf55be48,0x3f6d3ec4,0xbf7bbf0e,
0x3f35bf80,0x3e483f0e,0xbf6d3ec4,0x3f55bf7b,0x3f350000,0xbf7b3f55,0x3ec4bf6d,0x3f0e3e48,0xbf353f80,0xbe48bf0e,0x3f6dbec4,0xbf553f7b,
0xbf350000,0x3f7bbf55,0xbec43f6d,0xbf0ebe48,0xbf800000,0x3f6d3ec4,0xbf35bf35,0x3ec43f6d,0x3f800000,0xbf6dbec4,0x3f353f35,0xbec4bf6d,
0xbf800000,0x3f6d3ec4,0xbf35bf35,0x3ec43f6d,0x3f800000,0xbf6dbec4,0x3f353f35,0xbec4bf6d,0x3f800000,0xbec43f6d,0xbf35bf35,0x3f6dbec4,
0xbf800000,0x3ec4bf6d,0x3f353f35,0xbf6d3ec4,0x3f800000,0xbec43f6d,0xbf35bf35,0x3f6dbec4,0xbf800000,0x3ec4bf6d,0x3f353f35,0xbf6d3ec4,
0x3f35bf80,0xbf7b3f55,0x3f6dbec4,0xbf0ebe48,0x3f350000,0xbe48bf0e,0xbec43f6d,0x3f55bf7b,0xbf353f80,0x3f7bbf55,0xbf6d3ec4,0x3f0e3e48,
0xbf350000,0x3e483f0e,0x3ec4bf6d,0xbf553f7b,0xbf35bf80,0x3f553e48,0x3ec43f6d,0xbf7bbf0e,0xbf350000,0xbf0ebf7b,0x3f6d3ec4,0x3e483f55,
0x3f353f80,0xbf55be48,0xbec4bf6d,0x3f7b3f0e,0x3f350000,0x3f0e3f7b,0xbf6dbec4,0xbe48bf55,0,0x3f803f80,0,0xbf80bf80,
0,0x3f803f80,0,0xbf80bf80,0,0x3f803f80,0,0xbf80bf80,0,0x3f803f80,0,0xbf80bf80,
0,0xbf353f35,0xbf803f80,0xbf353f35,0,0xbf353f35,0xbf803f80,0xbf353f35,0,0xbf353f35,0xbf803f80,0xbf353f35,
0,0xbf353f35,0xbf803f80,0xbf353f35,0xbf35bf80,0xbf55be48,0x3ec43f6d,0x3f7b3f0e,0xbf350000,0x3f0e3f7b,0x3f6d3ec4,0xbe48bf55,
0x3f353f80,0x3f553e48,0xbec4bf6d,0xbf7bbf0e,0x3f350000,0xbf0ebf7b,0xbf6dbec4,0x3e483f55,0x3f35bf80,0x3f7bbf55,0x3f6dbec4,0x3f0e3e48,
0x3f350000,0x3e483f0e,0xbec43f6d,0xbf553f7b,0xbf353f80,0xbf7b3f55,0xbf6d3ec4,0xbf0ebe48,0xbf350000,0xbe48bf0e,0x3ec4bf6d,0x3f55bf7b,
0xbf800000,0xbec43f6d,0x3f353f35,0x3f6dbec4,0x3f800000,0x3ec4bf6d,0xbf35bf35,0xbf6d3ec4,0xbf800000,0xbec43f6d,0x3f353f35,0x3f6dbec4,
0x3f800000,0x3ec4bf6d,0xbf35bf35,0xbf6d3ec4,0x3f800000,0x3f6d3ec4,0x3f353f35,0x3ec43f6d,0xbf800000,0xbf6dbec4,0xbf35bf35,0xbec4bf6d,
0x3f800000,0x3f6d3ec4,0x3f353f35,0x3ec43f6d,0xbf800000,0xbf6dbec4,0xbf35bf35,0xbec4bf6d,0x3f35bf80,0xbe48bf0e,0xbf6d3ec4,0xbf553f7b,
0x3f350000,0x3f7bbf55,0x3ec4bf6d,0xbf0ebe48,0xbf353f80,0x3e483f0e,0x3f6dbec4,0x3f55bf7b,0xbf350000,0xbf7b3f55,0xbec43f6d,0x3f0e3e48,
0xbf35bf80,0xbf0ebf7b,0xbec4bf6d,0xbe48bf55,0xbf350000,0xbf55be48,0xbf6dbec4,0xbf7bbf0e,0x3f353f80,0x3f0e3f7b,0x3ec43f6d,0x3e483f55,
0x3f350000,0x3f553e48,0x3f6d3ec4,0x3f7b3f0e,0x3f803f80,0x3f803f80,0x3f803f80,0x3f803f80,0x3f803f80,0x3f803f80,0x3f803f80,0x3f803f80,
0x3f803f80,0x3f803f80,0x3f803f80,0x3f803f80,0x3f803f80,0x3f803f80,0x3f803f80,0x3f803f80,0xbf6d3f6d,0xbec43ec4,0x3ec4bec4,0x3f6dbf6d,
0xbf6d3f6d,0xbec43ec4,0x3ec4bec4,0x3f6dbf6d,0xbf6d3f6d,0xbec43ec4,0x3ec4bec4,0x3f6dbf6d,0xbf6d3f6d,0xbec43ec4,0x3ec4bec4,0x3f6dbf6d,
0xbf46bdc9,0xbf62be95,0xbf75bef1,0xbf7fbf22,0x3f223f7f,0x3ef13f75,0x3e953f62,0x3dc93f46,0x3f463dc9,0x3f623e95,0x3f753ef1,0x3f7f3f22,
0xbf22bf7f,0xbef1bf75,0xbe95bf62,0xbdc9bf46,0x3f75bef1,0x3f46bf7f,0xbdc9bf22,0xbf623e95,0xbe953f62,0x3f223dc9,0x3f7fbf46,0x3ef1bf75,
0xbf753ef1,0xbf463f7f,0x3dc93f22,0x3f62be95,0x3e95bf62,0xbf22bdc9,0xbf7f3f46,0xbef13f75,0xbe483f7b,0xbf0e3f55,0xbf553f0e,0xbf7b3e48,
0x3e48bf7b,0x3f0ebf55,0x3f55bf0e,0x3f7bbe48,0xbe483f7b,0xbf0e3f55,0xbf553f0e,0xbf7b3e48,0x3e48bf7b,0x3f0ebf55,0x3f55bf0e,0x3f7bbe48,
0x3f0e3f55,0x3f7bbe48,0x3e48bf7b,0xbf55bf0e,0xbf0ebf55,0xbf7b3e48,0xbe483f7b,0x3f553f0e,0x3f0e3f55,0x3f7bbe48,0x3e48bf7b,0xbf55bf0e,
0xbf0ebf55,0xbf7b3e48,0xbe483f7b,0x3f553f0e,0xbef1be95,0x3dc9bf46,0x3f22bf7f,0x3f75bf62,0x3f62bf75,0x3f7fbf22,0x3f46bdc9,0x3e953ef1,
0x3ef13e95,0xbdc93f46,0xbf223f7f,0xbf753f62,0xbf623f75,0xbf7f3f22,0xbf463dc9,0xbe95bef1,0x3dc9bf22,0xbf75bf62,0xbef13e95,0x3f463f7f,
0xbf7fbf46,0xbe953ef1,0x3f623f75,0x3f22bdc9,0xbdc93f22,0x3f753f62,0x3ef1be95,0xbf46bf7f,0x3f7f3f46,0x3e95bef1,0xbf62bf75,0xbf223dc9,
0x3f353f35,0xbf35bf35,0xbf35bf35,0x3f353f35,0x3f353f35,0xbf35bf35,0xbf35bf35,0x3f353f35,0x3f353f35,0xbf35bf35,0xbf35bf35,0x3f353f35,
0x3f353f35,0xbf35bf35,0xbf35bf35,0x3f353f35,0xbec43ec4,0x3f6dbf6d,0xbf6d3f6d,0x3ec4bec4,0xbec43ec4,0x3f6dbf6d,0xbf6d3f6d,0x3ec4bec4,
0xbec43ec4,0x3f6dbf6d,0xbf6d3f6d,0x3ec4bec4,0xbec43ec4,0x3f6dbf6d,0xbf6d3f6d,0x3ec4bec4,0xbf7fbf46,0x3e95bef1,0x3f623f75,0xbf223dc9,
0xbdc93f22,0xbf75bf62,0x3ef1be95,0x3f463f7f,0x3f7f3f46,0xbe953ef1,0xbf62bf75,0x3f22bdc9,0x3dc9bf22,0x3f753f62,0xbef13e95,0xbf46bf7f,
0x3f62bf75,0xbf7f3f22,0x3f46bdc9,0xbe95bef1,0x3ef13e95,0x3dc9bf46,0xbf223f7f,0x3f75bf62,0xbf623f75,0x3f7fbf22,0xbf463dc9,0x3e953ef1,
0xbef1be95,0xbdc93f46,0x3f22bf7f,0xbf753f62,0xbf553f0e,0xbe48bf7b,0x3f7b3e48,0xbf0e3f55,0x3f55bf0e,0x3e483f7b,0xbf7bbe48,0x3f0ebf55,
0xbf553f0e,0xbe48bf7b,0x3f7b3e48,0xbf0e3f55,0x3f55bf0e,0x3e483f7b,0xbf7bbe48,0x3f0ebf55,0x3f7b3e48,0xbf55bf0e,0x3f0e3f55,0xbe48bf7b,
0xbf7bbe48,0x3f553f0e,0xbf0ebf55,0x3e483f7b,0x3f7b3e48,0xbf55bf0e,0x3f0e3f55,0xbe48bf7b,0xbf7bbe48,0x3f553f0e,0xbf0ebf55,0x3e483f7b,
0x3e95bf62,0x3f223dc9,0xbf7f3f46,0x3ef1bf75,0x3f75bef1,0xbf463f7f,0xbdc9bf22,0x3f62be95,0xbe953f62,0xbf22bdc9,0x3f7fbf46,0xbef13f75,
0xbf753ef1,0x3f46bf7f,0x3dc93f22,0xbf623e95,0xbf22bf7f,0x3ef13f75,0xbe95bf62,0x3dc93f46,0xbf46bdc9,0x3f623e95,0xbf75bef1,0x3f7f3f22,
0x3f223f7f,0xbef1bf75,0x3e953f62,0xbdc9bf46,0x3f463dc9,0xbf62be95,0x3f753ef1,0xbf7fbf22,0,0,0,0,
0,0,0,0,0,0,0,0,0,0,0,0,
0x3ec4bec4,0xbf6d3f6d,0x3f6dbf6d,0xbec43ec4,0x3ec4bec4,0xbf6d3f6d,0x3f6dbf6d,0xbec43ec4,0x3ec4bec4,0xbf6d3f6d,0x3f6dbf6d,0xbec43ec4,
0x3ec4bec4,0xbf6d3f6d,0x3f6dbf6d,0xbec43ec4,0xbf22bf7f,0x3ef13f75,0xbe95bf62,0x3dc93f46,0xbf46bdc9,0x3f623e95,0xbf75bef1,0x3f7f3f22,
0x3f223f7f,0xbef1bf75,0x3e953f62,0xbdc9bf46,0x3f463dc9,0xbf62be95,0x3f753ef1,0xbf7fbf22,0x3e95bf62,0x3f223dc9,0xbf7f3f46,0x3ef1bf75,
0x3f75bef1,0xbf463f7f,0xbdc9bf22,0x3f62be95,0xbe953f62,0xbf22bdc9,0x3f7fbf46,0xbef13f75,0xbf753ef1,0x3f46bf7f,0x3dc93f22,0xbf623e95,
0xbf7bbe48,0x3f553f0e,0xbf0ebf55,0x3e483f7b,0x3f7b3e48,0xbf55bf0e,0x3f0e3f55,0xbe48bf7b,0xbf7bbe48,0x3f553f0e,0xbf0ebf55,0x3e483f7b,
0x3f7b3e48,0xbf55bf0e,0x3f0e3f55,0xbe48bf7b,0x3f55bf0e,0x3e483f7b,0xbf7bbe48,0x3f0ebf55,0xbf553f0e,0xbe48bf7b,0x3f7b3e48,0xbf0e3f55,
0x3f55bf0e,0x3e483f7b,0xbf7bbe48,0x3f0ebf55,0xbf553f0e,0xbe48bf7b,0x3f7b3e48,0xbf0e3f55,0x3f62bf75,0xbf7f3f22,0x3f46bdc9,0xbe95bef1,
0x3ef13e95,0x3dc9bf46,0xbf223f7f,0x3f75bf62,0xbf623f75,0x3f7fbf22,0xbf463dc9,0x3e953ef1,0xbef1be95,0xbdc93f46,0x3f22bf7f,0xbf753f62,
0xbf7fbf46,0x3e95bef1,0x3f623f75,0xbf223dc9,0xbdc93f22,0xbf75bf62,0x3ef1be95,0x3f463f7f,0x3f7f3f46,0xbe953ef1,0xbf62bf75,0x3f22bdc9,
0x3dc9bf22,0x3f753f62,0xbef13e95,0xbf46bf7f,0xbf35bf35,0x3f353f35,0x3f353f35,0xbf35bf35,0xbf35bf35,0x3f353f35,0x3f353f35,0xbf35bf35,
0xbf35bf35,0x3f353f35,0x3f353f35,0xbf35bf35,0xbf35bf35,0x3f353f35,0x3f353f35,0xbf35bf35,0x3f6dbf6d,0x3ec4bec4,0xbec43ec4,0xbf6d3f6d,
0x3f6dbf6d,0x3ec4bec4,0xbec43ec4,0xbf6d3f6d,0x3f6dbf6d,0x3ec4bec4,0xbec43ec4,0xbf6d3f6d,0x3f6dbf6d,0x3ec4bec4,0xbec43ec4,0xbf6d3f6d,
0x3dc9bf22,0xbf75bf62,0xbef13e95,0x3f463f7f,0xbf7fbf46,0xbe953ef1,0x3f623f75,0x3f22bdc9,0xbdc93f22,0x3f753f62,0x3ef1be95,0xbf46bf7f,
0x3f7f3f46,0x3e95bef1,0xbf62bf75,0xbf223dc9,0xbef1be95,0x3dc9bf46,0x3f22bf7f,0x3f75bf62,0x3f62bf75,0x3f7fbf22,0x3f46bdc9,0x3e953ef1,
0x3ef13e95,0xbdc93f46,0xbf223f7f,0xbf753f62,0xbf623f75,0xbf7f3f22,0xbf463dc9,0xbe95bef1,0xbf0ebf55,0xbf7b3e48,0xbe483f7b,0x3f553f0e,
0x3f0e3f55,0x3f7bbe48,0x3e48bf7b,0xbf55bf0e,0xbf0ebf55,0xbf7b3e48,0xbe483f7b,0x3f553f0e,0x3f0e3f55,0x3f7bbe48,0x3e48bf7b,0xbf55bf0e,
0x3e48bf7b,0x3f0ebf55,0x3f55bf0e,0x3f7bbe48,0xbe483f7b,0xbf0e3f55,0xbf553f0e,0xbf7b3e48,0x3e48bf7b,0x3f0ebf55,0x3f55bf0e,0x3f7bbe48,
0xbe483f7b,0xbf0e3f55,0xbf553f0e,0xbf7b3e48,0x3f75bef1,0x3f46bf7f,0xbdc9bf22,0xbf623e95,0xbe953f62,0x3f223dc9,0x3f7fbf46,0x3ef1bf75,
0xbf753ef1,0xbf463f7f,0x3dc93f22,0x3f62be95,0x3e95bf62,0xbf22bdc9,0xbf7f3f46,0xbef13f75,0xbf46bdc9,0xbf62be95,0xbf75bef1,0xbf7fbf22,
0x3f223f7f,0x3ef13f75,0x3e953f62,0x3dc93f46,0x3f463dc9,0x3f623e95,0x3f753ef1,0x3f7f3f22,0xbf22bf7f,0xbef1bf75,0xbe95bf62,0xbdc9bf46,
0,0,0,0,0,0,0,0,0,0,0,0,
0,0,0,0,0x3ec4bec4,0x3f6dbf6d,0x3f6dbf6d,0x3ec4bec4,0x3ec4bec4,0x3f6dbf6d,0x3f6dbf6d,0x3ec4bec4,
0x3ec4bec4,0x3f6dbf6d,0x3f6dbf6d,0x3ec4bec4,0x3ec4bec4,0x3f6dbf6d,0x3f6dbf6d,0x3ec4bec4,0xbf22bf7f,0xbef1bf75,0xbe95bf62,0xbdc9bf46,
0xbf46bdc9,0xbf62be95,0xbf75bef1,0xbf7fbf22,0x3f223f7f,0x3ef13f75,0x3e953f62,0x3dc93f46,0x3f463dc9,0x3f623e95,0x3f753ef1,0x3f7f3f22,
0x3e95bf62,0xbf22bdc9,0xbf7f3f46,0xbef13f75,0x3f75bef1,0x3f46bf7f,0xbdc9bf22,0xbf623e95,0xbe953f62,0x3f223dc9,0x3f7fbf46,0x3ef1bf75,
0xbf753ef1,0xbf463f7f,0x3dc93f22,0x3f62be95,0xbf7bbe48,0xbf55bf0e,0xbf0ebf55,0xbe48bf7b,0x3f7b3e48,0x3f553f0e,0x3f0e3f55,0x3e483f7b,
0xbf7bbe48,0xbf55bf0e,0xbf0ebf55,0xbe48bf7b,0x3f7b3e48,0x3f553f0e,0x3f0e3f55,0x3e483f7b,0x3f55bf0e,0xbe48bf7b,0xbf7bbe48,0xbf0e3f55,
0xbf553f0e,0x3e483f7b,0x3f7b3e48,0x3f0ebf55,0x3f55bf0e,0xbe48bf7b,0xbf7bbe48,0xbf0e3f55,0xbf553f0e,0x3e483f7b,0x3f7b3e48,0x3f0ebf55,
0x3f62bf75,0x3f7fbf22,0x3f46bdc9,0x3e953ef1,0x3ef13e95,0xbdc93f46,0xbf223f7f,0xbf753f62,0xbf623f75,0xbf7f3f22,0xbf463dc9,0xbe95bef1,
0xbef1be95,0x3dc9bf46,0x3f22bf7f,0x3f75bf62,0xbf7fbf46,0xbe953ef1,0x3f623f75,0x3f22bdc9,0xbdc93f22,0x3f753f62,0x3ef1be95,0xbf46bf7f,
0x3f7f3f46,0x3e95bef1,0xbf62bf75,0xbf223dc9,0x3dc9bf22,0xbf75bf62,0xbef13e95,0x3f463f7f,0xbf35bf35,0xbf35bf35,0x3f353f35,0x3f353f35,
0xbf35bf35,0xbf35bf35,0x3f353f35,0x3f353f35,0xbf35bf35,0xbf35bf35,0x3f353f35,0x3f353f35,0xbf35bf35,0xbf35bf35,0x3f353f35,0x3f353f35,
0x3f6dbf6d,0xbec43ec4,0xbec43ec4,0x3f6dbf6d,0x3f6dbf6d,0xbec43ec4,0xbec43ec4,0x3f6dbf6d,0x3f6dbf6d,0xbec43ec4,0xbec43ec4,0x3f6dbf6d,
0x3f6dbf6d,0xbec43ec4,0xbec43ec4,0x3f6dbf6d,0x3dc9bf22,0x3f753f62,0xbef13e95,0xbf46bf7f,0xbf7fbf46,0x3e95bef1,0x3f623f75,0xbf223dc9,
0xbdc93f22,0xbf75bf62,0x3ef1be95,0x3f463f7f,0x3f7f3f46,0xbe953ef1,0xbf62bf75,0x3f22bdc9,0xbef1be95,0xbdc93f46,0x3f22bf7f,0xbf753f62,
0x3f62bf75,0xbf7f3f22,0x3f46bdc9,0xbe95bef1,0x3ef13e95,0x3dc9bf46,0xbf223f7f,0x3f75bf62,0xbf623f75,0x3f7fbf22,0xbf463dc9,0x3e953ef1,
0xbf0ebf55,0x3f7bbe48,0xbe483f7b,0xbf55bf0e,0x3f0e3f55,0xbf7b3e48,0x3e48bf7b,0x3f553f0e,0xbf0ebf55,0x3f7bbe48,0xbe483f7b,0xbf55bf0e,
0x3f0e3f55,0xbf7b3e48,0x3e48bf7b,0x3f553f0e,0x3e48bf7b,0xbf0e3f55,0x3f55bf0e,0xbf7b3e48,0xbe483f7b,0x3f0ebf55,0xbf553f0e,0x3f7bbe48,
0x3e48bf7b,0xbf0e3f55,0x3f55bf0e,0xbf7b3e48,0xbe483f7b,0x3f0ebf55,0xbf553f0e,0x3f7bbe48,0x3f75bef1,0xbf463f7f,0xbdc9bf22,0x3f62be95,
0xbe953f62,0xbf22bdc9,0x3f7fbf46,0xbef13f75,0xbf753ef1,0x3f46bf7f,0x3dc93f22,0xbf623e95,0x3e95bf62,0x3f223dc9,0xbf7f3f46,0x3ef1bf75,
0xbf46bdc9,0x3f623e95,0xbf75bef1,0x3f7f3f22,0x3f223f7f,0xbef1bf75,0x3e953f62,0xbdc9bf46,0x3f463dc9,0xbf62be95,0x3f753ef1,0xbf7fbf22,
0xbf22bf7f,0x3ef13f75,0xbe95bf62,0x3dc93f46,0xbf80bf80,0x3f803f80,0xbf80bf80,0x3f803f80,0xbf80bf80,0x3f803f80,0xbf80bf80,0x3f803f80,
0xbf80bf80,0x3f803f80,0xbf80bf80,0x3f803f80,0xbf80bf80,0x3f803f80,0xbf80bf80,0x3f803f80,0x3f6dbf6d,0xbec43ec4,0xbec43ec4,0x3f6dbf6d,
0x3f6dbf6d,0xbec43ec4,0xbec43ec4,0x3f6dbf6d,0x3f6dbf6d,0xbec43ec4,0xbec43ec4,0x3f6dbf6d,0x3f6dbf6d,0xbec43ec4,0xbec43ec4,0x3f6dbf6d,
0x3f463dc9,0xbf62be95,0x3f753ef1,0xbf7fbf22,0xbf22bf7f,0x3ef13f75,0xbe95bf62,0x3dc93f46,0xbf46bdc9,0x3f623e95,0xbf75bef1,0x3f7f3f22,
0x3f223f7f,0xbef1bf75,0x3e953f62,0xbdc9bf46,0xbf753ef1,0x3f46bf7f,0x3dc93f22,0xbf623e95,0x3e95bf62,0x3f223dc9,0xbf7f3f46,0x3ef1bf75,
0x3f75bef1,0xbf463f7f,0xbdc9bf22,0x3f62be95,0xbe953f62,0xbf22bdc9,0x3f7fbf46,0xbef13f75,0x3e48bf7b,0xbf0e3f55,0x3f55bf0e,0xbf7b3e48,
0xbe483f7b,0x3f0ebf55,0xbf553f0e,0x3f7bbe48,0x3e48bf7b,0xbf0e3f55,0x3f55bf0e,0xbf7b3e48,0xbe483f7b,0x3f0ebf55,0xbf553f0e,0x3f7bbe48,
0xbf0ebf55,0x3f7bbe48,0xbe483f7b,0xbf55bf0e,0x3f0e3f55,0xbf7b3e48,0x3e48bf7b,0x3f553f0e,0xbf0ebf55,0x3f7bbe48,0xbe483f7b,0xbf55bf0e,
0x3f0e3f55,0xbf7b3e48,0x3e48bf7b,0x3f553f0e,0x3ef13e95,0x3dc9bf46,0xbf223f7f,0x3f75bf62,0xbf623f75,0x3f7fbf22,0xbf463dc9,0x3e953ef1,
0xbef1be95,0xbdc93f46,0x3f22bf7f,0xbf753f62,0x3f62bf75,0xbf7f3f22,0x3f46bdc9,0xbe95bef1,0xbdc93f22,0xbf75bf62,0x3ef1be95,0x3f463f7f,
0x3f7f3f46,0xbe953ef1,0xbf62bf75,0x3f22bdc9,0x3dc9bf22,0x3f753f62,0xbef13e95,0xbf46bf7f,0xbf7fbf46,0x3e95bef1,0x3f623f75,0xbf223dc9,
0xbf35bf35,0xbf35bf35,0x3f353f35,0x3f353f35,0xbf35bf35,0xbf35bf35,0x3f353f35,0x3f353f35,0xbf35bf35,0xbf35bf35,0x3f353f35,0x3f353f35,
0xbf35bf35,0xbf35bf35,0x3f353f35,0x3f353f35,0x3ec4bec4,0x3f6dbf6d,0x3f6dbf6d,0x3ec4bec4,0x3ec4bec4,0x3f6dbf6d,0x3f6dbf6d,0x3ec4bec4,
0x3ec4bec4,0x3f6dbf6d,0x3f6dbf6d,0x3ec4bec4,0x3ec4bec4,0x3f6dbf6d,0x3f6dbf6d,0x3ec4bec4,0x3f7f3f46,0x3e95bef1,0xbf62bf75,0xbf223dc9,
0x3dc9bf22,0xbf75bf62,0xbef13e95,0x3f463f7f,0xbf7fbf46,0xbe953ef1,0x3f623f75,0x3f22bdc9,0xbdc93f22,0x3f753f62,0x3ef1be95,0xbf46bf7f,
0xbf623f75,0xbf7f3f22,0xbf463dc9,0xbe95bef1,0xbef1be95,0x3dc9bf46,0x3f22bf7f,0x3f75bf62,0x3f62bf75,0x3f7fbf22,0x3f46bdc9,0x3e953ef1,
0x3ef13e95,0xbdc93f46,0xbf223f7f,0xbf753f62,0x3f55bf0e,0xbe48bf7b,0xbf7bbe48,0xbf0e3f55,0xbf553f0e,0x3e483f7b,0x3f7b3e48,0x3f0ebf55,
0x3f55bf0e,0xbe48bf7b,0xbf7bbe48,0xbf0e3f55,0xbf553f0e,0x3e483f7b,0x3f7b3e48,0x3f0ebf55,0xbf7bbe48,0xbf55bf0e,0xbf0ebf55,0xbe48bf7b,
0x3f7b3e48,0x3f553f0e,0x3f0e3f55,0x3e483f7b,0xbf7bbe48,0xbf55bf0e,0xbf0ebf55,0xbe48bf7b,0x3f7b3e48,0x3f553f0e,0x3f0e3f55,0x3e483f7b,
0xbe953f62,0x3f223dc9,0x3f7fbf46,0x3ef1bf75,0xbf753ef1,0xbf463f7f,0x3dc93f22,0x3f62be95,0x3e95bf62,0xbf22bdc9,0xbf7f3f46,0xbef13f75,
0x3f75bef1,0x3f46bf7f,0xbdc9bf22,0xbf623e95,0x3f223f7f,0x3ef13f75,0x3e953f62,0x3dc93f46,0x3f463dc9,0x3f623e95,0x3f753ef1,0x3f7f3f22,
0xbf22bf7f,0xbef1bf75,0xbe95bf62,0xbdc9bf46,0xbf46bdc9,0xbf62be95,0xbf75bef1,0xbf7fbf22,0x3f803f80,0,0x3f803f80,0,
0x3f803f80,0,0x3f803f80,0,0x3f803f80,0,0x3f803f80,0,0x3f803f80,0,0x3f803f80,0,
0x3f803f80,0,0x3f803f80,0,0x3f803f80,0,0x3f803f80,0,0x3f803f80,0,0x3f803f80,0,
0x3f803f80,0,0x3f803f80,0,0x3f803f80,0,0x3f803f80,0,0x3f803f80,0,0x3f803f80,0,
0x3f803f80,0,0x3f803f80,0,0x3f803f80,0,0x3f803f80,0,0x3f803f80,0,0x3f803f80,0,
0x3f803f80,0,0x3f803f80,0,0x3f803f80,0,0x3f803f80,0,0x3f803f80,0,0x3f803f80,0,
0x3f7f3f80,0xbda10000,0x3f793f7d,0xbe6fbe20,0x3f7f3f80,0xbdc9bca1,0x3f783f7c,0xbe81be34,0x3f7e3f80,0xbdf1bd21,0x3f763f7b,0xbe8bbe48,
0x3f7e3f80,0xbe0cbd71,0x3f753f7a,0xbe95be5b,0x3f7f3f80,0xbdb5bc21,0x3f783f7c,0xbe79be2a,0x3f7f3f80,0xbdddbcf1,0x3f773f7c,0xbe86be3e,
0x3f7e3f80,0xbe02bd49,0x3f763f7b,0xbe90be52,0x3f7d3f7f,0xbe16bd8d,0x3f743f7a,0xbe99be65,0x3f6d3f73,0xbec4be9e,0x3f5a3f64,0xbf06bee8,
0x3f6b3f72,0xbecdbea8,0x3f583f62,0xbf0abef1,0x3f683f70,0xbed6beb1,0x3f553f5f,0xbf0ebefa,0x3f663f6e,0xbedfbebb,0x3f523f5d,0xbf12bf01,
0x3f6c3f73,0xbec9bea3,0x3f593f63,0xbf08beed,0x3f6a3f71,0xbed2beac,0x3f563f61,0xbf0cbef6,0x3f673f6f,0xbedbbeb6,0x3f533f5e,0xbf10beff,
0x3f653f6d,0xbee4bebf,0x3f513f5c,0xbf14bf04,0x3f7d3f80,0xbe200000,0x3f643f73,0xbee8be9e,0x3f7b3f80,0xbe48bd21,0x3f5f3f70,0xbefabeb1,
0x3f793f7f,0xbe6fbda1,0x3f5a3f6d,0xbf06bec4,0x3f763f7e,0xbe8bbdf1,0x3f553f68,0xbf0ebed6,0x3f7c3f80,0xbe34bca1,0x3f623f72,0xbef1bea8,
0x3f7a3f80,0xbe5bbd71,0x3f5d3f6e,0xbf01bebb,0x3f783f7f,0xbe81bdc9,0x3f583f6b,0xbf0abecd,0x3f753f7e,0xbe95be0c,0x3f523f66,0xbf12bedf,
0x3f353f4f,0xbf35bf16,0x3ee83f16,0xbf64bf4f,0x3f2e3f49,0xbf3cbf1e,0x3ed63f0e,0xbf68bf55,0x3f263f43,0xbf43bf26,0x3ec43f06,0xbf6dbf5a,
0x3f1e3f3c,0xbf49bf2e,0x3eb13efa,0xbf70bf5f,0x3f313f4c,0xbf39bf1b,0x3edf3f12,0xbf66bf52,0x3f2a3f46,0xbf3fbf22,0x3ecd3f0a,0xbf6bbf58,
0x3f223f3f,0xbf46bf2a,0x3ebb3f01,0xbf6ebf5d,0x3f1b3f39,0xbf4cbf31,0x3ea83ef1,0xbf72bf62,0x3f793f80,0xbe6f0000,0x3f433f64,0xbf26bee8,
0x3f753f80,0xbe95bd71,0x3f393f5d,0xbf31bf01,0x3f703f7e,0xbeb1bdf1,0x3f2e3f55,0xbf3cbf0e,0x3f6b3f7c,0xbecdbe34,0x3f223f4c,0xbf46bf1b,
0x3f773f80,0xbe86bcf1,0x3f3e3f61,0xbf2cbef6,0x3f733f7f,0xbea3bdb5,0x3f333f59,0xbf37bf08,0x3f6d3f7d,0xbebfbe16,0x3f283f51,0xbf41bf14,
0x3f673f7b,0xbedbbe52,0x3f1d3f47,0xbf4bbf20,0x3ec43f16,0xbf6dbf4f,0xbda13e20,0xbf7fbf7d,0x3ea83f0a,0xbf72bf58,0xbe0c3dc9,0xbf7ebf7f,
0x3e8b3efa,0xbf76bf5f,0xbe483d21,0xbf7bbf80,0x3e5b3edf,0xbf7abf66,0xbe81bca1,0xbf78bf80,0x3eb63f10,0xbf6fbf53,0xbddd3e02,0xbf7fbf7e,
0x3e993f04,0xbf74bf5c,0xbe2a3d8d,0xbf7cbf7f,0x3e793eed,0xbf78bf63,0xbe653c21,0xbf7abf80,0x3e3e3ed2,0xbf7cbf6a,0xbe90bd49,0xbf76bf80,
0x3f733f80,0xbe9e0000,0x3f163f4f,0xbf4fbf16,0x3f6d3f7f,0xbec4bda1,0x3f063f43,0xbf5abf26,0x3f643f7d,0xbee8be20,0x3ee83f35,0xbf64bf35,
0x3f5a3f79,0xbf06be6f,0x3ec43f26,0xbf6dbf43,0x3f703f80,0xbeb1bd21,0x3f0e3f49,0xbf55bf1e,0x3f683f7e,0xbed6bdf1,0x3efa3f3c,0xbf5fbf2e,
0x3f5f3f7b,0xbefabe48,0x3ed63f2e,0xbf68bf3c,0x3f553f76,0xbf0ebe8b,0x3eb13f1e,0xbf70bf49,0x3e9e,0xbf80bf73,0xbf16be9e,0xbf4fbf73,
0xbda13e6f,0xbf7fbf79,0xbf26bec4,0xbf43bf6d,0xbe203e20,0xbf7dbf7d,0xbf35bee8,0xbf35bf64,0xbe6f3da1,0xbf79bf7f,0xbf43bf06,0xbf26bf5a,
0xbd213e8b,0xbf80bf76,0xbf1ebeb1,0xbf49bf70,0xbdf13e48,0xbf7ebf7b,0xbf2ebed6,0xbf3cbf68,0xbe483df1,0xbf7bbf7e,0xbf3cbefa,0xbf2ebf5f,
0xbe8b3d21,0xbf76bf80,0xbf49bf0e,0xbf1ebf55,0x3f6d3f80,0xbec40000,0x3ec43f35,0xbf6dbf35,0x3f623f7f,0xbef1bdc9,0x3e953f22,0xbf75bf46,
0x3f553f7b,0xbf0ebe48,0x3e483f0e,0xbf7bbf55,0x3f463f75,0xbf22be95,0x3dc93ef1,0xbf7fbf62,0x3f673f80,0xbedbbd49,0x3eac3f2c,0xbf71bf3e,
0x3f5c3f7d,0xbf04be16,0x3e793f18,0xbf78bf4e,0x3f4e3f78,0xbf18be79,0x3e163f04,0xbf7dbf5c,0x3f3e3f71,0xbf2cbeac,0x3d493edb,0xbf80bf67,
0xbec40000,0xbf6dbf80,0xbf6dbf35,0xbec4bf35,0xbef1bdc9,0xbf62bf7f,0xbf75bf46,0xbe95bf22,0xbf0ebe48,0xbf55bf7b,0xbf7bbf55,0xbe48bf0e,
0xbf22be95,0xbf46bf75,0xbf7fbf62,0xbdc9bef1,0xbedbbd49,0xbf67bf80,0xbf71bf3e,0xbeacbf2c,0xbf04be16,0xbf5cbf7d,0xbf78bf4e,0xbe79bf18,
0xbf18be79,0xbf4ebf78,0xbf7dbf5c,0xbe16bf04,0xbf2cbeac,0xbf3ebf71,0xbf80bf67,0xbd49bedb,0x3f643f80,0xbee80000,0x3e203f16,0xbf7dbf4f,
0x3f553f7e,0xbf0ebdf1,0x3d213efa,0xbf80bf5f,0x3f433f79,0xbf26be6f,0xbda13ec4,0xbf7fbf6d,0x3f2e3f70,0xbf3cbeb1,0xbe483e8b,0xbf7bbf76,
0x3f5d3f80,0xbf01bd71,0x3dc93f0a,0xbf7fbf58,0x3f4c3f7c,0xbf1bbe34,0xbca13edf,0xbf80bf66,0x3f393f75,0xbf31be95,0xbe0c3ea8,0xbf7ebf72,
0x3f223f6b,0xbf46becd,0xbe813e5b,0xbf78bf7a,0xbf35be9e,0xbf35bf73,0xbf7dbf73,0x3e20be9e,0xbf49bed6,0xbf1ebf68,0xbf76bf7b,0x3e8bbe48,
0xbf5abf06,0xbf06bf5a,0xbf6dbf7f,0x3ec4bda1,0xbf68bf1e,0xbed6bf49,0xbf5fbf80,0x3efa3d21,0xbf3fbebb,0xbf2abf6e,0xbf7abf78,0x3e5bbe81,
0xbf52bef1,0xbf12bf62,0xbf72bf7e,0x3ea8be0c,0xbf62bf12,0xbef1bf52,0xbf66bf80,0x3edfbca1,0xbf6ebf2a,0xbebbbf3f,0xbf58bf7f,0x3f0a3dc9,
0x3f5a3f80,0xbf060000,0xbda13ee8,0xbf7fbf64,0x3f463f7e,0xbf22be0c,0xbe5b3ea8,0xbf7abf72,0x3f2e3f76,0xbf3cbe8b,0xbeb13e48,0xbf70bf7b,
0x3f123f6b,0xbf52becd,0xbef13d71,0xbf62bf80,0x3f513f7f,0xbf14bd8d,0xbe163ec9,0xbf7dbf6c,0x3f3a3f7b,0xbf30be52,0xbe903e86,0xbf76bf77,
0x3f203f71,0xbf47beac,0xbed23e02,0xbf6abf7e,0x3f043f63,0xbf5cbeed,0xbf08bc21,0xbf59bf80,0xbf6dbf16,0xbec4bf4f,0xbf43bf7d,0x3f263e20,
0xbf78bf31,0xbe81bf39,0xbf2abf75,0x3f3f3e95,0xbf7ebf49,0xbdf1bf1e,0xbf0ebf68,0x3f553ed6,0xbf80bf5d,0x3ca1bf01,0xbedfbf58,0x3f663f0a,
0xbf73bf24,0xbea3bf44,0xbf37bf7a,0x3f333e65,0xbf7cbf3e,0xbe3ebf2c,0xbf1dbf6f,0x3f4b3eb6,0xbf80bf53,0xbd49bf10,0xbeffbf61,0x3f5e3ef6,
0xbf7fbf65,0x3db5bee4,0xbebfbf4e,0x3f6d3f18,0x3f4f3f80,0xbf160000,0xbe9e3e9e,0xbf73bf73,0x3f353f7d,0xbf35be20,0xbee83e20,0xbf64bf7d,
0x3f163f73,0xbf4fbe9e,0xbf160000,0xbf4fbf80,0x3ee83f64,0xbf64bee8,0xbf35be20,0xbf35bf7d,0x3f433f7f,0xbf26bda1,0xbec43e6f,0xbf6dbf79,
0x3f263f79,0xbf43be6f,0xbf063da1,0xbf5abf7f,0x3f063f6d,0xbf5abec4,0xbf26bda1,0xbf43bf7f,0x3ec43f5a,0xbf6dbf06,0xbf43be6f,0xbf26bf79,
0xbf80bf4f,0xbf16,0xbe9ebf4f,0x3f733f16,0xbf7dbf64,0x3e20bee8,0xbe20bf35,0x3f7d3f35,0xbf73bf73,0x3e9ebe9e,0xbf16,0x3f803f4f,
0xbf64bf7d,0x3ee8be20,0x3e20bee8,0x3f7d3f64,0xbf7fbf5a,0x3da1bf06,0xbe6fbf43,0x3f793f26,0xbf79bf6d,0x3e6fbec4,0xbda1bf26,0x3f7f3f43,
0xbf6dbf79,0x3ec4be6f,0x3da1bf06,0x3f7f3f5a,0xbf5abf7f,0x3f06bda1,0x3e6fbec4,0x3f793f6d,0x3f433f80,0xbf260000,0xbf063e20,0xbf5abf7d,
0x3f223f7c,0xbf46be34,0xbf2abca1,0xbf3fbf80,0x3efa3f70,0xbf5fbeb1,0xbf49be48,0xbf1ebf7b,0x3ea83f5d,0xbf72bf01,0xbf62bebb,0xbef1bf6e,
0x3f333f7f,0xbf37bdb5,0xbf183d8d,0xbf4ebf7f,0x3f103f77,0xbf53be86,0xbf3abddd,0xbf30bf7f,0x3ed23f67,0xbf6abedb,0xbf56be90,0xbf0cbf76,
0x3e793f51,0xbf78bf14,0xbf6cbee4,0xbec9bf65,0xbf6dbf73,0x3ec4be9e,0x3e6fbee8,0x3f793f64,0xbf58bf7e,0x3f0abe0c,0x3ecdbe95,0x3f6b3f75,
0xbf3cbf80,0x3f2e3d21,0x3f0ebdf1,0x3f553f7e,0xbf1bbf7a,0x3f4c3e5b,0x3f313d71,0x3f393f80,0xbf63bf7a,0x3eedbe65,0x3ea3bebf,0x3f733f6d,
0xbf4bbf80,0x3f1dbd49,0x3ef6be52,0x3f613f7b,0xbf2cbf7e,0x3f3e3e02,0x3f20bcf1,0x3f473f80,0xbf08bf74,0x3f593e99,0x3f413e16,0x3f283f7d,
0x3f803f80,0,0x3f803f80,0,0x3f803f80,0,0x3f803f80,0,0x3f803f80,0,0x3f803f80,0,
0x3f803f80,0,0x3f803f80,0,0x3f803f80,0,0x3f803f80,0,0x3f803f80,0,0x3f803f80,0,
0x3f803f80,0,0x3f803f80,0,0x3f803f80,0,0x3f803f80,0,0x3f803f80,0,0x3f803f80,0,
0x3f803f80,0,0x3f803f80,0,0x3f803f80,0,0x3f803f80,0,0x3f803f80,0,0x3f803f80,0,
0x3f803f80,0,0x3f803f80,0,0x3f803f80,0,0x3f803f80,0,0x3f803f80,0,0x3f803f80,0,
0x3f803f80,0,0x3f803f80,0,0x3f803f80,0xbc210000,0x3f7f3f7f,0xbdb5bda1,0x3f803f80,0xbcf1bca1,0x3f7f3f7f,0xbdddbdc9,
0x3f803f80,0xbd49bd21,0x3f7e3f7e,0xbe02bdf1,0x3f7f3f80,0xbd8dbd71,0x3f7d3f7e,0xbe16be0c,0x3f7c3f7d,0xbe2abe20,0x3f783f79,0xbe79be6f,
0x3f7c3f7c,0xbe3ebe34,0x3f773f78,0xbe86be81,0x3f7b3f7b,0xbe52be48,0x3f763f76,0xbe90be8b,0x3f7a3f7a,0xbe65be5b,0x3f743f75,0xbe99be95,
0x3f733f73,0xbea3be9e,0x3f6c3f6d,0xbec9bec4,0x3f713f72,0xbeacbea8,0x3f6a3f6b,0xbed2becd,0x3f6f3f70,0xbeb6beb1,0x3f673f68,0xbedbbed6,
0x3f6d3f6e,0xbebfbebb,0x3f653f66,0xbee4bedf,0x3f633f64,0xbeedbee8,0x3f593f5a,0xbf08bf06,0x3f613f62,0xbef6bef1,0x3f563f58,0xbf0cbf0a,
0x3f5e3f5f,0xbeffbefa,0x3f533f55,0xbf10bf0e,0x3f5c3f5d,0xbf04bf01,0x3f513f52,0xbf14bf12,0x3f803f80,0xbca10000,0x3f7c3f7d,0xbe34be20,
0x3f803f80,0xbd71bd21,0x3f7a3f7b,0xbe5bbe48,0x3f7f3f7f,0xbdc9bda1,0x3f783f79,0xbe81be6f,0x3f7e3f7e,0xbe0cbdf1,0x3f753f76,0xbe95be8b,
0x3f723f73,0xbea8be9e,0x3f623f64,0xbef1bee8,0x3f6e3f70,0xbebbbeb1,0x3f5d3f5f,0xbf01befa,0x3f6b3f6d,0xbecdbec4,0x3f583f5a,0xbf0abf06,
0x3f663f68,0xbedfbed6,0x3f523f55,0xbf12bf0e,0x3f4c3f4f,0xbf1bbf16,0x3f313f35,0xbf39bf35,0x3f463f49,0xbf22bf1e,0x3f2a3f2e,0xbf3fbf3c,
0x3f3f3f43,0xbf2abf26,0x3f223f26,0xbf46bf43,0x3f393f3c,0xbf31bf2e,0x3f1b3f1e,0xbf4cbf49,0x3f123f16,0xbf52bf4f,0x3edf3ee8,0xbf66bf64,
0x3f0a3f0e,0xbf58bf55,0x3ecd3ed6,0xbf6bbf68,0x3f013f06,0xbf5dbf5a,0x3ebb3ec4,0xbf6ebf6d,0x3ef13efa,0xbf62bf5f,0x3ea83eb1,0xbf72bf70,
0x3f803f80,0xbcf10000,0x3f773f79,0xbe86be6f,0x3f7f3f80,0xbdb5bd71,0x3f733f75,0xbea3be95,0x3f7d3f7e,0xbe16bdf1,0x3f6d3f70,0xbebfbeb1,
0x3f7b3f7c,0xbe52be34,0x3f673f6b,0xbedbbecd,0x3f613f64,0xbef6bee8,0x3f3e3f43,0xbf2cbf26,0x3f593f5d,0xbf08bf01,0x3f333f39,0xbf37bf31,
0x3f513f55,0xbf14bf0e,0x3f283f2e,0xbf41bf3c,0x3f473f4c,0xbf20bf1b,0x3f1d3f22,0xbf4bbf46,0x3f103f16,0xbf53bf4f,0x3eb63ec4,0xbf6fbf6d,
0x3f043f0a,0xbf5cbf58,0x3e993ea8,0xbf74bf72,0x3eed3efa,0xbf63bf5f,0x3e793e8b,0xbf78bf76,0x3ed23edf,0xbf6abf66,0x3e3e3e5b,0xbf7cbf7a,
0x3e023e20,0xbf7ebf7d,0xbdddbda1,0xbf7fbf7f,0x3d8d3dc9,0xbf7fbf7f,0xbe2abe0c,0xbf7cbf7e,0x3c213d21,0xbf80bf80,0xbe65be48,0xbf7abf7b,
0xbd49bca1,0xbf80bf80,0xbe90be81,0xbf76bf78,0x3f803f80,0xbd210000,0x3f703f73,0xbeb1be9e,0x3f7e3f7f,0xbdf1bda1,0x3f683f6d,0xbed6bec4,
0x3f7b3f7d,0xbe48be20,0x3f5f3f64,0xbefabee8,0x3f763f79,0xbe8bbe6f,0x3f553f5a,0xbf0ebf06,0x3f493f4f,0xbf1ebf16,0x3f0e3f16,0xbf55bf4f,
0x3f3c3f43,0xbf2ebf26,0x3efa3f06,0xbf5fbf5a,0x3f2e3f35,0xbf3cbf35,0x3ed63ee8,0xbf68bf64,0x3f1e3f26,0xbf49bf43,0x3eb13ec4,0xbf70bf6d,
0x3e8b3e9e,0xbf76bf73,0xbd210000,0xbf80bf80,0x3e483e6f,0xbf7bbf79,0xbdf1bda1,0xbf7ebf7f,0x3df13e20,0xbf7ebf7d,0xbe48be20,0xbf7bbf7d,
0x3d213da1,0xbf80bf7f,0xbe8bbe6f,0xbf76bf79,0xbeb1be9e,0xbf70bf73,0xbf1ebf16,0xbf49bf4f,0xbed6bec4,0xbf68bf6d,0xbf2ebf26,0xbf3cbf43,
0xbefabee8,0xbf5fbf64,0xbf3cbf35,0xbf2ebf35,0xbf0ebf06,0xbf55bf5a,0xbf49bf43,0xbf1ebf26,0x3f803f80,0xbd490000,0x3f673f6d,0xbedbbec4,
0x3f7d3f7f,0xbe16bdc9,0x3f5c3f62,0xbf04bef1,0x3f783f7b,0xbe79be48,0x3f4e3f55,0xbf18bf0e,0x3f713f75,0xbeacbe95,0x3f3e3f46,0xbf2cbf22,
0x3f2c3f35,0xbf3ebf35,0x3eac3ec4,0xbf71bf6d,0x3f183f22,0xbf4ebf46,0x3e793e95,0xbf78bf75,0x3f043f0e,0xbf5cbf55,0x3e163e48,0xbf7dbf7b,
0x3edb3ef1,0xbf67bf62,0x3d493dc9,0xbf80bf7f,0xbd490000,0xbf80bf80,0xbedbbec4,0xbf67bf6d,0xbe16bdc9,0xbf7dbf7f,0xbf04bef1,0xbf5cbf62,
0xbe79be48,0xbf78bf7b,0xbf18bf0e,0xbf4ebf55,0xbeacbe95,0xbf71bf75,0xbf2cbf22,0xbf3ebf46,0xbf3ebf35,0xbf2cbf35,0xbf71bf6d,0xbeacbec4,
0xbf4ebf46,0xbf18bf22,0xbf78bf75,0xbe79be95,0xbf5cbf55,0xbf04bf0e,0xbf7dbf7b,0xbe16be48,0xbf67bf62,0xbedbbef1,0xbf80bf7f,0xbd49bdc9,
0x3f803f80,0xbd710000,0x3f5d3f64,0xbf01bee8,0x3f7c3f7e,0xbe34bdf1,0x3f4c3f55,0xbf1bbf0e,0x3f753f79,0xbe95be6f,0x3f393f43,0xbf31bf26,
0x3f6b3f70,0xbecdbeb1,0x3f223f2e,0xbf46bf3c,0x3f0a3f16,0xbf58bf4f,0x3dc93e20,0xbf7fbf7d,0x3edf3efa,0xbf66bf5f,0xbca13d21,0xbf80bf80,
0x3ea83ec4,0xbf72bf6d,0xbe0cbda1,0xbf7ebf7f,0x3e5b3e8b,0xbf7abf76,0xbe81be48,0xbf78bf7b,0xbebbbe9e,0xbf6ebf73,0xbf3fbf35,0xbf2abf35,
0xbef1bed6,0xbf62bf68,0xbf52bf49,0xbf12bf1e,0xbf12bf06,0xbf52bf5a,0xbf62bf5a,0xbef1bf06,0xbf2abf1e,0xbf3fbf49,0xbf6ebf68,0xbebbbed6,
0xbf78bf73,0xbe81be9e,0xbf7abf7d,0x3e5b3e20,0xbf7ebf7b,0xbe0cbe48,0xbf72bf76,0x3ea83e8b,0xbf80bf7f,0xbca1bda1,0xbf66bf6d,0x3edf3ec4,
0xbf7fbf80,0x3dc93d21,0xbf58bf5f,0x3f0a3efa,0x3f7f3f80,0xbd8d0000,0x3f513f5a,0xbf14bf06,0x3f7b3f7e,0xbe52be0c,0x3f3a3f46,0xbf30bf22,
0x3f713f76,0xbeacbe8b,0x3f203f2e,0xbf47bf3c,0x3f633f6b,0xbeedbecd,0x3f043f12,0xbf5cbf52,0x3ec93ee8,0xbf6cbf64,0xbe16bda1,0xbf7dbf7f,
0x3e863ea8,0xbf77bf72,0xbe90be5b,0xbf76bf7a,0x3e023e48,0xbf7ebf7b,0xbed2beb1,0xbf6abf70,0xbc213d71,0xbf80bf80,0xbf08bef1,0xbf59bf62,
0xbf24bf16,0xbf44bf4f,0xbf73bf6d,0xbea3bec4,0xbf3ebf31,0xbf2cbf39,0xbf7cbf78,0xbe3ebe81,0xbf53bf49,0xbf10bf1e,0xbf80bf7e,0xbd49bdf1,
0xbf65bf5d,0xbee4bf01,0xbf7fbf80,0x3db53ca1,0xbf7abf7d,0x3e653e20,0xbf37bf43,0x3f333f26,0xbf6fbf75,0x3eb63e95,0xbf1dbf2a,0x3f4b3f3f,
0xbf61bf68,0x3ef63ed6,0xbeffbf0e,0x3f5e3f55,0xbf4ebf58,0x3f183f0a,0xbebfbedf,0x3f6d3f66,0x3f7f3f80,0xbda10000,0x3f433f4f,0xbf26bf16,
0x3f793f7d,0xbe6fbe20,0x3f263f35,0xbf43bf35,0x3f6d3f73,0xbec4be9e,0x3f063f16,0xbf5abf4f,0x3f5a3f64,0xbf06bee8,0x3ec43ee8,0xbf6dbf64,
0x3e6f3e9e,0xbf79bf73,0xbec4be9e,0xbf6dbf73,0x3da13e20,0xbf7fbf7d,0xbf06bee8,0xbf5abf64,0xbda10000,0xbf7fbf80,0xbf26bf16,0xbf43bf4f,
0xbe6fbe20,0xbf79bf7d,0xbf43bf35,0xbf26bf35,0xbf5abf4f,0xbf06bf16,0xbf7fbf80,0x3da10000,0xbf6dbf64,0xbec4bee8,0xbf79bf7d,0x3e6f3e20,
0xbf79bf73,0xbe6fbe9e,0xbf6dbf73,0x3ec43e9e,0xbf7fbf7d,0xbda1be20,0xbf5abf64,0x3f063ee8,0xbf43bf4f,0x3f263f16,0xbe6fbe9e,0x3f793f73,
0xbf26bf35,0x3f433f35,0xbda1be20,0x3f7f3f7d,0xbf06bf16,0x3f5a3f4f,0x3da10000,0x3f7f3f80,0xbec4bee8,0x3f6d3f64,0x3e6f3e20,0x3f793f7d,
0x3f7f3f80,0xbdb50000,0x3f333f43,0xbf37bf26,0x3f773f7c,0xbe86be34,0x3f103f22,0xbf53bf46,0x3f673f70,0xbedbbeb1,0x3ed23efa,0xbf6abf5f,
0x3f513f5d,0xbf14bf01,0x3e793ea8,0xbf78bf72,0x3d8d3e20,0xbf7fbf7d,0xbf18bf06,0xbf4ebf5a,0xbdddbca1,0xbf7fbf80,0xbf3abf2a,0xbf30bf3f,
0xbe90be48,0xbf76bf7b,0xbf56bf49,0xbf0cbf1e,0xbee4bebb,0xbf65bf6e,0xbf6cbf62,0xbec9bef1,0xbf7abf73,0xbe65be9e,0xbf63bf6d,0x3eed3ec4,
0xbf80bf7e,0xbd49be0c,0xbf4bbf58,0x3f1d3f0a,0xbf7ebf80,0x3e023d21,0xbf2cbf3c,0x3f3e3f2e,0xbf74bf7a,0x3e993e5b,0xbf08bf1b,0x3f593f4c,
0xbebfbee8,0x3f6d3f64,0x3ea33e6f,0x3f733f79,0xbe52be95,0x3f7b3f75,0x3ef63ecd,0x3f613f6b,0xbcf1bdf1,0x3f803f7e,0x3f203f0e,0x3f473f55,
0x3e163d71,0x3f7d3f80,0x3f413f31,0x3f283f39,
};
constexpr uint32_t FFT_F_BYTES = 43008, FFT_A_BYTES = 40960, FFT_BOX = 5376, FFT_PITCH = 336, FFT_TAB_BYTES = 13312, FFT_PARK = 22528;

__device__ __forceinline__ uint32_t h2add(uint32_t a, uint32_t b){ uint32_t r; asm("add.rn.bf16x2 %0,%1,%2;":"=r"(r):"r"(a),"r"(b)); return r; }
__device__ __forceinline__ uint32_t h2sub(uint32_t a, uint32_t b){ uint32_t r; asm("sub.rn.bf16x2 %0,%1,%2;":"=r"(r):"r"(a),"r"(b)); return r; }
__device__ __forceinline__ uint32_t h2mul(uint32_t a, uint32_t b){ uint32_t r; asm("mul.rn.bf16x2 %0,%1,%2;":"=r"(r):"r"(a),"r"(b)); return r; }
__device__ __forceinline__ uint32_t h2fma(uint32_t a, uint32_t b, uint32_t c){ uint32_t r; asm("fma.rn.bf16x2 %0,%1,%2,%3;":"=r"(r):"r"(a),"r"(b),"r"(c)); return r; }
__device__ __forceinline__ uint32_t h2mms(uint32_t a, uint32_t b, uint32_t c, uint32_t d){
  uint32_t r; asm("{\n.reg .b32 t, u;\nmul.bf16x2 u,%1,%2;\nmul.bf16x2 t,%3,%4;\nsub.bf16x2 %0,u,t;\n}":"=r"(r):"r"(a),"r"(b),"r"(c),"r"(d)); return r; }
__device__ __forceinline__ uint32_t h2mma(uint32_t a, uint32_t b, uint32_t c, uint32_t d){ return h2fma(a,b,h2mul(c,d)); }

constexpr uint32_t H5_C1 = 0x3E9E3E9Eu, H5_C2 = 0xBF4FBF4Fu, H5_S1 = 0x3F733F73u, H5_NS1 = 0xBF73BF73u, H5_S2 = 0x3F163F16u, H5_NS2 = 0xBF16BF16u,
                   H5_Q1 = 0x3F1E3F1Eu, H5_Q2 = 0xBFCFBFCFu;
template<int SGN>
__device__ __forceinline__ void radix5h(uint32_t (&r)[5], uint32_t (&i)[5]){
  const uint32_t t1r=h2add(r[1],r[4]), t1i=h2add(i[1],i[4]), t2r=h2add(r[2],r[3]), t2i=h2add(i[2],i[3]);
  const uint32_t t3r=h2sub(r[1],r[4]), t3i=h2sub(i[1],i[4]), t4r=h2sub(r[2],r[3]), t4i=h2sub(i[2],i[3]);
  const uint32_t m1r=h2fma(H5_C2,t2r,h2fma(H5_C1,t1r,r[0])), m1i=h2fma(H5_C2,t2i,h2fma(H5_C1,t1i,i[0]));
  const uint32_t m2r=h2fma(H5_C1,t2r,h2fma(H5_C2,t1r,r[0])), m2i=h2fma(H5_C1,t2i,h2fma(H5_C2,t1i,i[0]));
  const uint32_t n1r=h2fma(H5_Q1,t4r,t3r), n1i=h2fma(H5_Q1,t4i,t3i);
  const uint32_t n2r=h2fma(H5_Q2,t4r,t3r), n2i=h2fma(H5_Q2,t4i,t3i);
  r[0]=h2add(h2add(r[0],t1r),t2r); i[0]=h2add(h2add(i[0],t1i),t2i);
  constexpr uint32_t P1 = SGN<0? H5_S1 : H5_NS1, M1 = SGN<0? H5_NS1 : H5_S1, P2 = SGN<0? H5_S2 : H5_NS2, M2 = SGN<0? H5_NS2 : H5_S2;
  r[1]=h2fma(P1,n1i,m1r); i[1]=h2fma(M1,n1r,m1i); r[4]=h2fma(M1,n1i,m1r); i[4]=h2fma(P1,n1r,m1i);
  r[2]=h2fma(P2,n2i,m2r); i[2]=h2fma(M2,n2r,m2i); r[3]=h2fma(M2,n2i,m2r); i[3]=h2fma(P2,n2r,m2i);
}
__device__ __forceinline__ void cs_frac(int num, int den, float inv_den, float& c, float& s){
  int n = (2*num>den)? num-den : num;
  float a = (float)n * (6.283185307179586f*inv_den);
  c = __cosf(a); s = __sinf(a);
}
template<int N> __device__ __forceinline__ void fence_u32(uint32_t (&a)[N]){
  #pragma unroll
  for(int i=0;i<N;i++) asm volatile("":"+r"(a[i])::"memory");
}
__device__ __forceinline__ uint4 lds128(uint32_t addr){ uint4 v; asm volatile("ld.shared.v4.u32 {%0,%1,%2,%3}, [%4];":"=r"(v.x),"=r"(v.y),"=r"(v.z),"=r"(v.w):"r"(addr)); return v; }
__device__ __forceinline__ void sts128(uint32_t addr, uint32_t a, uint32_t b, uint32_t c, uint32_t d){ asm volatile("st.shared.v4.u32 [%0], {%1,%2,%3,%4};"::"r"(addr),"r"(a),"r"(b),"r"(c),"r"(d):"memory"); }
__device__ __forceinline__ void lds128v(uint32_t addr, uint32_t& a, uint32_t& b, uint32_t& c, uint32_t& d){ asm volatile("ld.shared.v4.u32 {%0,%1,%2,%3}, [%4];":"=r"(a),"=r"(b),"=r"(c),"=r"(d):"r"(addr):"memory"); }
__device__ __forceinline__ void park16(uint32_t addr, const uint32_t (&y)[16]){
  #pragma unroll
  for(int q=0;q<4;q++) sts128(addr + q*2048, y[4*q], y[4*q+1], y[4*q+2], y[4*q+3]);
}
__device__ __forceinline__ void unpark16(uint32_t addr, uint32_t (&y)[16]){
  #pragma unroll
  for(int q=0;q<4;q++) asm volatile("ld.shared.v4.u32 {%0,%1,%2,%3}, [%4];":"=r"(y[4*q]),"=r"(y[4*q+1]),"=r"(y[4*q+2]),"=r"(y[4*q+3]):"r"(addr + q*2048):"memory");
}
__device__ __forceinline__ uint32_t lds16(uint32_t addr){ uint32_t v; asm volatile("ld.shared.u16 %0, [%1];":"=r"(v):"r"(addr)); return v; }

__device__ __forceinline__ void fft_unit(uint32_t sF, uint32_t sA, uint32_t sT, uint32_t sP, uint32_t vbar, uint32_t fbar, uint32_t tbar_off, uint32_t ebar_off, int k1, int barid, long long* prof){
  const int tid = threadIdx.x & 127, w = __shfl_sync(0xffffffffu, tid>>5, 0), lane = tid&31, g = lane>>2, t = lane&3;
  const int p = w>>1;
  const int tile = lane>>3, r8 = lane&7;
  const uint32_t sTwA = sT + 8192 + t*16, sTwB = sT + 8192 + 2560 + t*16;
  {
    const int s2 = 8*(w&1)+g;
    const float nrm = 1.0f/(2048.0f*640.0f);
    #pragma unroll
    for(int hi=0;hi<2;hi++){
      float cr[2], ci[2];
      #pragma unroll
      for(int e=0;e<2;e++){ int k2=8*hi+2*t+e; int ks=k1+128*k2; float c,s; cs_frac((s2*ks)&2047,2048,1.f/2048,c,s); cr[e]=c*nrm; ci[e]=s*nrm; }
      const uint32_t q0 = pack_bf16(cr[0],cr[1]), q1 = pack_bf16(ci[0],ci[1]);
      asm volatile("st.shared.v2.u32 [%0], {%1,%2};"::"r"(sP + 20480 + hi*1024 + tid*8),"r"(q0),"r"(q1):"memory");
    }
  }
  uint32_t A1[4][4];
  {
    const int k2 = 8*(w&1)+g; const int ks = k1+128*k2;
    float cr[4], ci[4];
    #pragma unroll
    for(int q=0;q<4;q++){ int s2 = 2*t + (q&1) + 8*(q>>1); float c,s; cs_frac((s2*ks)&2047,2048,1.f/2048,c,s); cr[q]=c; ci[q]=-s; }
    const bool sp0=(k1==0), sp64=(k1==64);
    #pragma unroll
    for(int ri=0;ri<2;ri++){
      float vre[4], vim[4];
      #pragma unroll
      for(int q=0;q<4;q++){
        float a_re = (ri==0)? cr[q] : -ci[q]; float a_im = (ri==0)? ci[q] : cr[q];
        if(ri==1){ if(sp64){ a_re=cr[q]; a_im=ci[q]; } if(sp0){ a_re=0.f; a_im=0.f; } }
        else if(sp64){ a_re=0.f; a_im=0.f; }
        vre[q]=a_re; vim[q]=a_im;
      }
      A1[ri][0]=pack_bf16(vre[0],vre[1]); A1[ri][1]=pack_bf16(vim[0],vim[1]);
      A1[ri][2]=pack_bf16(vre[2],vre[3]); A1[ri][3]=pack_bf16(vim[2],vim[3]);
      const uint32_t sg = p? 0x80008000u : 0u;
      #pragma unroll
      for(int q=0;q<4;q++) A1[2+ri][q]=A1[ri][q]^sg;
    }
  }
  if(prof && tid==0) prof[0]=clock64();
  mbar_wait(vbar, 0);
  if(prof && tid==0) prof[1]=clock64();
  uint32_t Y[5][16];
  {
    float acc[5][16];
    auto issue = [&](const int h){
      const uint32_t dA = desc_lo(sA + h*64, 0);
      wg_fence();
      #pragma unroll
      for(int kk=0;kk<4;kk++){
        #pragma unroll
        for(int a2=0;a2<5;a2++){
          const int a1=kk>>1, ri=kk&1; const int a=(5*a1+2*a2)%10;
          wgmma_rs_n32<1>(acc[a2], A1[kk][0],A1[kk][1],A1[kk][2],A1[kk][3], mk_desc<1024>(dA + ((ri*20480+a*2048)>>4)), kk>0);
        }
      }
      wg_commit();
    };
    issue(0);
    mbar_wait(sT + tbar_off, 0);
    #pragma unroll
    for(int h=0;h<2;h++){
      wg_wait<0>();
      #pragma unroll
      for(int a2=0;a2<5;a2++) fence_regs(acc[a2]);
      uint32_t yr[2][2][5], yi[2][2][5];
      #pragma unroll
      for(int e=0;e<2;e++){
        #pragma unroll
        for(int jp=0;jp<2;jp++){
          #pragma unroll
          for(int a2=0;a2<5;a2++){ yr[e][jp][a2]=pack_bf16(acc[a2][8*jp+e],acc[a2][8*jp+4+e]); yi[e][jp][a2]=pack_bf16(acc[a2][8*jp+2+e],acc[a2][8*jp+6+e]); }
        }
      }
      fence_u32(yr[0][0]); fence_u32(yr[0][1]); fence_u32(yr[1][0]); fence_u32(yr[1][1]);
      fence_u32(yi[0][0]); fence_u32(yi[0][1]); fence_u32(yi[1][0]); fence_u32(yi[1][1]);
      if(h==0) issue(1);
      #pragma unroll
      for(int e=0;e<2;e++){
        radix5h<-1>(yr[e][0], yi[e][0]); radix5h<-1>(yr[e][1], yi[e][1]);
        int ka = 5*p;
        #pragma unroll
        for(int c=0;c<5;c++){
          const uint4 tw = lds128(sTwA + ((ka*2 + h)*2 + e)*64);
          Y[c][8*e+4*h]   = h2mms(yr[e][0][c],tw.x,yi[e][0][c],tw.y);
          Y[c][8*e+4*h+1] = h2mma(yr[e][0][c],tw.y,yi[e][0][c],tw.x);
          Y[c][8*e+4*h+2] = h2mms(yr[e][1][c],tw.z,yi[e][1][c],tw.w);
          Y[c][8*e+4*h+3] = h2mma(yr[e][1][c],tw.w,yi[e][1][c],tw.z);
          if(h==0) sts128(sP + (2*c+e)*2048 + tid*16, Y[c][8*e], Y[c][8*e+1], Y[c][8*e+2], Y[c][8*e+3]);
          ka += 6; if(ka>=10) ka-=10;
        }
      }
    }
  }
  if(prof && tid==0) prof[2]=clock64();
  mbar_wait(fbar, 0);
  if(prof && tid==0) prof[3]=clock64();
  {
    const int k2 = 8*(w&1)+g, k2m = (k1==0)? ((16-k2)&15) : 15-k2;
    const int k1m = (128-k1)&127, oD = k1&7, oM0 = k1m&7, oM1 = (k1m+1)&7;
    const uint32_t fD0 = sF + k2*FFT_PITCH + 2*oD + 20*t;
    const uint32_t fM1 = sF + 4*FFT_BOX + k2m*FFT_PITCH + 2*(oM1+159) - 20*t, fM0 = sF + 6*FFT_BOX + k2m*FFT_PITCH + 2*(oM0+160) - 20*t;
    const uint32_t dK = desc_lo(sT,16), dN = desc_lo(sT,2048);
    float de[32], dq[32];
    uint32_t wr[8], wi[8];
    auto load_filter = [&](const int ka, const bool sym){
      const uint32_t fD = fD0 + 2*ka, fMa = fM1 - 2*ka, fMb = fM0 - 2*ka;
      #pragma unroll
      for(int jn=0;jn<8;jn++){
        const uint32_t b0 = (jn<4)? fD + (2*(jn>>1))*FFT_BOX + 160*(jn&1) : ((jn<6)? fMa : fMb) - 160*(jn&1);
        const uint32_t b1 = (jn<4)? b0 + 80 : b0 - 80;
        wr[jn] = __byte_perm(lds16(b0), lds16(b1), 0x5410);
        wi[jn] = __byte_perm(lds16(b0+FFT_BOX), lds16(b1+FFT_BOX), 0x5410);
      }
      if(sym){
        const uint32_t aM = sF + 6*FFT_BOX + k2m*FFT_PITCH + 2*oM0, aD = sF + 2*FFT_BOX + k2*FFT_PITCH + 2*(oD+160);
        const float m0r = bf_lo(lds16(aM)), m0i = bf_lo(lds16(aM+FFT_BOX)), d3r = bf_lo(lds16(aD)), d3i = bf_lo(lds16(aD+FFT_BOX));
        const uint32_t r0 = pack_bf16(0.5f*(bf_lo(wr[0])+m0r), bf_hi(wr[0])), i0 = pack_bf16(0.5f*(bf_lo(wi[0])-m0i), bf_hi(wi[0]));
        const uint32_t r4 = pack_bf16(0.5f*(bf_lo(wr[4])+d3r), bf_hi(wr[4])), i4 = pack_bf16(0.5f*(bf_lo(wi[4])-d3i), bf_hi(wi[4]));
        if(t==0){ wr[0]=r0; wi[0]=i0; wr[4]=r4; wi[4]=i4; }
      }
    };
    auto issue_fwd = [&](const uint32_t (&y)[16]){
      wg_fence();
      #pragma unroll
      for(int s=0;s<2;s++) wgmma_rs_n64<0>(de, y[4*s],y[4*s+1],y[4*s+2],y[4*s+3], mk_desc<512,2>(dK+2*s), s>0);
      #pragma unroll
      for(int s=0;s<2;s++) wgmma_rs_n64<0>(dq, y[8+4*s],y[8+4*s+1],y[8+4*s+2],y[8+4*s+3], mk_desc<512,2>(dK+256+2*s), s>0);
      wg_commit();
    };
    auto unpark_in = [&](const int c){
      #pragma unroll
      for(int e=0;e<2;e++) lds128v(sP + (2*c+e)*2048 + tid*16, Y[c][8*e], Y[c][8*e+1], Y[c][8*e+2], Y[c][8*e+3]);
    };
    int ka = 5*p;
    unpark_in(0);
    issue_fwd(Y[0]);
    load_filter(ka, p==0);
    #pragma unroll
    for(int c=0;c<5;c++){
      wg_wait<0>(); fence_regs(de); fence_regs(dq);
      uint32_t x0r[4], x0i[4], x1r[4], x1i[4];
      #pragma unroll
      for(int jn=0;jn<4;jn++){
        float er[2], ei[2], orr[2], oi[2];
        #pragma unroll
        for(int e=0;e<2;e++){
          er[e]  = de[4*jn+e] - de[4*(jn+4)+2+e]; ei[e] = de[4*(jn+4)+e] + de[4*jn+2+e];
          orr[e] = dq[4*jn+e] - dq[4*(jn+4)+2+e]; oi[e] = dq[4*(jn+4)+e] + dq[4*jn+2+e];
        }
        x0r[jn] = pack_bf16(er[0]+orr[0], er[1]+orr[1]); x0i[jn] = pack_bf16(ei[0]+oi[0], ei[1]+oi[1]);
        x1r[jn] = pack_bf16(er[0]-orr[0], er[1]-orr[1]); x1i[jn] = pack_bf16(ei[0]-oi[0], ei[1]-oi[1]);
      }
      uint32_t zp[8], zm[8];
      #pragma unroll
      for(int jn=0;jn<4;jn++){
        const uint32_t z0r = h2mms(x0r[jn],wr[jn],x0i[jn],wi[jn]),     z0i = h2mma(x0r[jn],wi[jn],x0i[jn],wr[jn]);
        const uint32_t z1r = h2mma(x1r[jn],wr[jn+4],x1i[jn],wi[jn+4]), z1i = h2mms(x1i[jn],wr[jn+4],x1r[jn],wi[jn+4]);
        zp[2*jn] = h2add(z0r,z1r); zp[2*jn+1] = h2add(z0i,z1i);
        zm[2*jn] = h2sub(z0r,z1r); zm[2*jn+1] = h2sub(z0i,z1i);
      }
      fence_u32(zp); fence_u32(zm);
      wg_fence();
      #pragma unroll
      for(int s=0;s<2;s++) wgmma_rs_n64<1>(de, zp[4*s],zp[4*s+1],zp[4*s+2],zp[4*s+3], mk_desc<512,2>(dN+64*s), s>0);
      #pragma unroll
      for(int s=0;s<2;s++) wgmma_rs_n64<1>(dq, zm[4*s],zm[4*s+1],zm[4*s+2],zm[4*s+3], mk_desc<512,2>(dN+256+64*s), s>0);
      wg_commit();
      const int kan = (ka+6>=10)? ka-4 : ka+6;
      if(c<4){ unpark_in(c+1); load_filter(kan, false); }
      wg_wait<0>(); fence_regs(de); fence_regs(dq);
      uint32_t tr[8], ti[8];
      #pragma unroll
      for(int j=0;j<8;j++){
        const int jn=j>>1, e2=j&1;
        tr[j] = pack_bf16(de[4*jn+e2] + de[4*(jn+4)+2+e2], dq[4*jn+e2] + dq[4*(jn+4)+2+e2]);
        ti[j] = pack_bf16(de[4*jn+2+e2] - de[4*(jn+4)+e2], dq[4*jn+2+e2] - dq[4*(jn+4)+e2]);
      }
      fence_u32(tr); fence_u32(ti);
      if(c<4) issue_fwd(Y[c+1]);
      #pragma unroll
      for(int jp=0;jp<4;jp++){
        const uint4 tw = lds128(sTwB + (ka*4 + jp)*64);
        Y[c][4*jp]   = h2mma(tr[2*jp],tw.x,ti[2*jp],tw.y);
        Y[c][4*jp+1] = h2mms(ti[2*jp],tw.x,tr[2*jp],tw.y);
        Y[c][4*jp+2] = h2mma(tr[2*jp+1],tw.z,ti[2*jp+1],tw.w);
        Y[c][4*jp+3] = h2mms(ti[2*jp+1],tw.z,tr[2*jp+1],tw.w);
      }
      ka = kan;
    }
  }
  if(prof && tid==0) prof[4]=clock64();
  named_bar(barid,128);
  {
    const uint32_t erow = sA + (16*w + 8*(tile&1) + r8)*128;
    #pragma unroll
    for(int jj=0;jj<4;jj++){
      uint32_t r0[5],i0[5],r1[5],i1[5];
      #pragma unroll
      for(int c=0;c<5;c++){ r0[c]=Y[c][4*jj]; i0[c]=Y[c][4*jj+1]; r1[c]=Y[c][4*jj+2]; i1[c]=Y[c][4*jj+3]; }
      radix5h<1>(r0,i0); radix5h<1>(r1,i1);
      const uint32_t ad = erow + (((2*jj + (tile>>1)) ^ r8)<<4);
      #pragma unroll
      for(int a2=0;a2<5;a2++) stmatrix_x4(ad + a2*8192, r0[a2],i0[a2],r1[a2],i1[a2]);
    }
  }
  uint32_t A9[4][4];
  #pragma unroll
  for(int hi=0;hi<2;hi++){
    uint32_t q0, q1; asm volatile("ld.shared.v2.u32 {%0,%1}, [%2];":"=r"(q0),"=r"(q1):"r"(sP + 20480 + hi*1024 + tid*8):"memory");
    A9[hi][0]=q0; A9[hi][1]=q1; A9[hi][2]=q1^0x80008000u; A9[hi][3]=q0;
    const uint32_t sg = p? 0x80008000u : 0u;
    #pragma unroll
    for(int i=0;i<4;i++) A9[2+hi][i]=A9[hi][i]^sg;
  }
  fence_async_smem();
  named_bar(barid,128);
  mbar_arrive_if(sT + ebar_off, tid==0); mbar_arrive_if(sT + ebar_off + 8, tid==0);
  if(prof && tid==0) prof[5]=clock64();
  {
    const int a1 = w>>1;
    const int s2 = 8*(w&1) + r8;
    const uint32_t rbase = sF + (tile&1)*20480 + s2*128;
    float acc[2][32];
    const uint32_t dE = desc_lo(sA, 0);
    auto issue = [&](float (&acc)[32], const int a2){
      wg_fence();
      #pragma unroll
      for(int kk=0;kk<4;kk++)
        wgmma_rs_n64<1>(acc, A9[kk][0],A9[kk][1],A9[kk][2],A9[kk][3], mk_desc<1024>(dE + ((a2*8192+kk*2048)>>4)), kk>0);
      wg_commit();
    };
    issue(acc[0],0); issue(acc[1],1);
    int a = 5*a1;
    auto drain = [&](float (&acc)[32], const int a2){
      if(a2<4) wg_wait<1>(); else wg_wait<0>();
      fence_regs(acc);
      uint32_t o[16];
      #pragma unroll
      for(int q=0;q<16;q++) o[q] = pack_bf16(acc[2*q],acc[2*q+1]);
      fence_u32(o);
      if(a2<3) issue(acc, a2+2);
      #pragma unroll
      for(int jj=0;jj<4;jj++)
        stmatrix_x4(rbase + a*2048 + (((2*jj + (tile>>1)) ^ r8)<<4), o[4*jj], o[4*jj+1], o[4*jj+2], o[4*jj+3]);
      a += 2; if(a>=10) a-=10;
    };
    drain(acc[0],0); drain(acc[1],1); drain(acc[0],2); drain(acc[1],3); drain(acc[0],4);
  }
  fence_async_smem();
  named_bar(barid,128);
  if(prof && tid==0) prof[6]=clock64();
}
__device__ __forceinline__ void fft_issue_v(const CUtensorMap* tmV, uint32_t sA, uint32_t vbar, int k1){
  const int r0 = (k1==0||k1==64)? 0 : 2*k1;
  mbar_expect_tx(vbar, 40960);
  tma_load_4d(sA,       tmV,0,0,0,r0,  vbar);
  tma_load_4d(sA+20480, tmV,0,0,0,r0+1,vbar);
}
__device__ __forceinline__ void fft_issue_f(const CUtensorMap* tmWr, const CUtensorMap* tmWi, uint32_t sF, uint32_t fbar, int k1){
  const int e0 = k1*321, e1 = ((128-k1)&127)*321;
  mbar_expect_tx(fbar, FFT_F_BYTES);
  #pragma unroll 1
  for(int q=0;q<4;q++){
    const int e = (q==0? e0 : q==1? e0+160 : q==2? e1+161 : e1) & ~7;
    tma_load_2d(sF+(2*q)*FFT_BOX, tmWr, e, 0, fbar); tma_load_2d(sF+(2*q+1)*FFT_BOX, tmWi, e, 0, fbar);
  }
}
constexpr int NCTA = 132;
constexpr int NUNIT = 27;
constexpr uint32_t SM_X = 0, SM_W = 163840, SM_MISC = 229376, SM_TOTAL = 232448;
constexpr int W_NST = 4;
constexpr uint32_t SM_FT = 0, SM_FP = FFT_TAB_BYTES, SM_FA = SM_FP + 2*FFT_PARK, SM_FF = SM_FA + 2*FFT_A_BYTES;
static_assert(SM_FA%1024==0 && SM_FA>=2*26624 && SM_FF>=5*26624 && SM_FF+2*FFT_F_BYTES<=229376, "FFT layout");
constexpr uint32_t G2_STAGE = 26624; constexpr int G2_NST = 8;
constexpr uint32_t SM_GW = SM_MISC + 1024;
constexpr uint32_t B_XFULL = 0, B_WFULL = 80, B_WEMPTY = 112, B_XFREE = 144, B_VFULL = 152  , B_TAB = 168,
                   B_G2FULL = 176  , B_G2EMPTY = 240  , B_GATE = 304, B_EPOCH = 312, B_TURN = 320, B_GW = 328, B_GO = 336,
                   B_PUBV = 344, B_PUBH = 352  , B_PUBU = 384  ,
                   B_FFULL = 400  , B_VFREE = 416;
constexpr int NBAR = 53;

#define MAP_M(b) ((((b)>>2)&3) + 4*(((b)>>4)&3))
#define MAP_J(b) (((b)&3) + 4*((b)>>6))
constexpr int RING5 = 9;
__device__ uint4    g_h[16*NUNIT*1024];
__device__ uint4    g_wdp[8*NUNIT*640];
__device__ uint4    g_V[128*16*640*2/16];
__device__ uint4    g_U[16*128*640*2/16];
__device__ float    g_gate[2048];
__device__ unsigned g_hflag[16*32];
__device__ unsigned g_cnt[16*32];

struct Params {
  CUtensorMap tm_x, tm_wg, tm_wu, tm_vld, tm_ust, tm_uld, tm_out, tm_wr, tm_wi;
  const uint8_t* x; const uint8_t* wg; const uint8_t* wu;
  const uint8_t* wr; const uint8_t* wi; const uint8_t* wd; const uint16_t* gate_w;
  long long* prof;
};

#define SYMADDR(T, sym) ([&]{ uint64_t a_; asm volatile("mov.u64 %0, " #sym ";":"=l"(a_)); return (T*)a_; }())
__device__ __forceinline__ unsigned ld_acquire(const unsigned* p){ unsigned v; asm volatile("ld.acquire.gpu.global.u32 %0, [%1];":"=r"(v):"l"(p):"memory"); return v; }
__device__ __forceinline__ void red_release(unsigned* p, unsigned v){ asm volatile("red.release.gpu.global.add.u32 [%0], %1;"::"l"(p),"r"(v):"memory"); }
__device__ __forceinline__ void red_relaxed(unsigned* p, unsigned v){ asm volatile("red.relaxed.gpu.global.add.u32 [%0], %1;"::"l"(p),"r"(v):"memory"); }
__device__ __forceinline__ void st_release(unsigned* p, unsigned v){ asm volatile("st.release.gpu.global.u32 [%0], %1;"::"l"(p),"r"(v):"memory"); }
#define PROF(i) do{}while(0)

__device__ __forceinline__ void pf_line(const void* p){ asm volatile("prefetch.global.L2 [%0];"::"l"(p)); }
__device__ __forceinline__ void pf_weights(const uint8_t* wg_, const uint8_t* wu_, int u, int m, int idx){
  pf_line(((idx&1)? wu_ : wg_) + (size_t)((idx>>3)*64 + 4*m + ((idx>>1)&3))*3456 + u*128);
}
__device__ __forceinline__ int unit_of(int j, int i){ return (j<6)? j+6*i : (j==6? 24 : (j==7? 26 : 25)); }
__device__ __forceinline__ int kb_perm(int p, int k0, int k1){
  if(p==0) return k0; if(p==1) return k1;
  int v = p-2;
  if(k0==6 || k0==7){ v += 3; if(v>=k0) v++; return (v>=9)? v-9 : v; }
  if(v>=k0) v++; if(v>=k1) v++; return v;
}
struct TrueT{ static constexpr bool value=true; }; struct FalseT{ static constexpr bool value=false; };
__device__ __forceinline__ int g2_unit(int i){
  if(i<6) return i; if(i==6) return 24; if(i==7) return 26;
  return (i==26)? 25 : i-2;
}

__device__ __forceinline__ uint4 ldg_nc(const uint4* p){ uint4 v; asm volatile("ld.global.nc.v4.u32 {%0,%1,%2,%3}, [%4];":"=r"(v.x),"=r"(v.y),"=r"(v.z),"=r"(v.w):"l"(p)); return v; }
__global__ void __launch_bounds__(384,1) gated_mix_kernel(const __grid_constant__ Params P){
  extern __shared__ __align__(1024) uint8_t smem[];
  const int wg = __shfl_sync(0xffffffffu, (int)threadIdx.x>>7, 0);
  const int warp = __shfl_sync(0xffffffffu, (int)threadIdx.x>>5, 0);
  volatile unsigned* s_epoch = (volatile unsigned*)(smem + SM_MISC + 512);
  volatile unsigned* s_ready = (volatile unsigned*)(smem + SM_MISC + 520);
#define DERIVE() \
  uint32_t sb = smem_u32(smem), tx_, bx_; \
  asm volatile("mov.u32 %0, %0;":"+r"(sb)); asm volatile("mov.u32 %0, %%tid.x;":"=r"(tx_)); asm volatile("mov.u32 %0, %%ctaid.x;":"=r"(bx_)); \
  const uint32_t mb_ = sb + SM_MISC; const int b = (int)bx_, lane = tx_&31; const bool extra = (b>=128); \
  const int m = MAP_M(b), j = MAP_J(b); const bool isfft = extra? (b==128) : (j>=6); \
  const int nunits = extra? (b==128? 2 : (b==131? 4 : 5)) : (j<6? 4 : 1); \
  const int mbase = (b==128)? 0 : 5*b - 643;        \
  auto get_ep1 = [&]()->unsigned { mbar_wait(mb_+B_EPOCH,0); return *s_epoch; }; \
  (void)isfft; (void)nunits; (void)mbase; (void)get_ep1; (void)lane; (void)m; (void)extra

  if(wg==2){
    asm volatile("setmaxnreg.dec.sync.aligned.u32 40;");
    if(warp==8){
      DERIVE();
      if(elect_one()){
        #pragma unroll
        for(int i=0;i<10;i++) mbar_init(mb_+B_XFULL+8*i, 1);
        mbar_init(mb_+B_WFULL, 1);
        asm volatile("fence.mbarrier_init.release.cluster;":::"memory");
      }
      __syncwarp();
      unsigned ready = 0;
      auto wait_ready = [&](const unsigned need){
        if((ready&need)!=need){
          uint32_t it=0;
          for(;;){ ready = *s_ready; if((ready&need)==need) break; __nanosleep(20); if(++it>(1u<<22)) TIMEOUT(3001, need); }
          fence_async_global();
        }
      };
      {
        const int nst = nunits*10, k0 = extra? 0 : j, k1 = extra? 1 : 8+(j>>2);
        auto load_w = [&](const uint32_t d, const uint32_t br, const int f0, const int kb){
          mbar_expect_tx(br,16384); tma_load_2d(d,&P.tm_wg,f0,kb*64,br); tma_load_2d(d+8192,&P.tm_wu,f0,kb*64,br); };
        auto load_x = [&](const uint32_t d, const uint32_t br, const int mm, const int kb){
          mbar_expect_tx(br,16384); tma_load_3d(d,&P.tm_x,kb*64,mm,0,br); };
        int slot=0, ph=1, kb=0, f0=unit_of(j,0)*64, mm=mbase;
        #pragma unroll 1
        for(int c=0;c<nst;c++){
          if(c==1) asm volatile("bar.sync 0, 384;":::"memory");
          if(c>=4) mbar_wait(mb_+B_WEMPTY+8*slot, ph);
          if(c<7){
            #pragma unroll 1
            for(int q=0;q<((c<4)? 1 : 2);q++){
              const int x = kb_perm((c<4)? c : 2*c-4+q, k0, k1);
              if(elect_one()){ if(extra) load_w(sb+SM_X+x*16384, mb_+B_XFULL+8*x, 1600, x); else load_x(sb+SM_X+x*16384, mb_+B_XFULL+8*x, m, x); }
              __syncwarp();
            }
          }
          if(elect_one()){
            const uint32_t d = sb+SM_W+slot*16384, br = mb_+B_WFULL+8*slot;
            if(extra) load_x(d, br, mm, kb);
            else {
              load_w(d, br, f0, (c<10)? kb_perm(c, k0, k1) : kb);
              if(c==8) prefetch_l2(P.wd + (size_t)b*17280, 17280);
              if(c==9){ prefetch_l2(P.wr + (size_t)b*10272, 10272); prefetch_l2(P.wi + (size_t)b*10272, 10272); }
            }
          }
          __syncwarp();
          if(++slot==W_NST){slot=0; ph^=1;}
          if(++kb==10){kb=0; f0+=384; mm++;}
        }
      }
      mbar_wait(mb_+B_EPOCH,0);
      PROF(40);
      if(isfft){
        wait_ready(1u<<30);
        PROF(42);
        const int nu = extra? 1 : 2, k10 = extra? 64 : (4*m + 2*(j-6));
        mbar_wait(extra? mb_+B_XFREE : mb_+B_VFREE, 0);
        PROF(51);
        #pragma unroll 1
        for(int ps=0;ps<2*nu;ps++){
          const int u = nu-1 - ((ps>=nu)? ps-nu : ps);
          if(ps==nu){
            mbar_wait(mb_+B_XFREE,0);
            PROF(41);
            if(elect_one()){ mbar_expect_tx(mb_+B_TAB, FFT_TAB_BYTES); bulk_load(sb+SM_FT, SYMADDR(uint8_t, T_FFT), FFT_TAB_BYTES, mb_+B_TAB); }
            __syncwarp();
          }
          if(ps>=nu) mbar_wait(mb_+B_VFULL+8*u, 0);
          if(elect_one()){
            if(ps<nu) fft_issue_v(&P.tm_vld, sb+SM_FA+u*FFT_A_BYTES, mb_+B_VFULL+8*u, k10+u);
            else fft_issue_f(&P.tm_wr, &P.tm_wi, sb+SM_FF+u*FFT_F_BYTES, mb_+B_FFULL+8*u, k10+u);
          }
          __syncwarp();
          if(ps==0) PROF(60);
        }
      }
      if(!extra){
        wait_ready(1u<<28);
        PROF(11);
        int slot=0; uint32_t phm=0;
        #pragma unroll 1
        for(int i=0;i<29;i++){
          const int u = (i<NUNIT)? g2_unit(i) : 0;
          if(i<NUNIT){
            wait_ready(1u<<u);
          } else wait_ready(1u<<29);
          mbar_wait(mb_+B_G2EMPTY+8*slot, (phm>>slot)&1);
          phm ^= 1u<<slot;
          if(i==0) PROF(43);
          const uint32_t br = mb_+B_G2FULL+8*slot, d = sb + slot*G2_STAGE;
          if(i<NUNIT){
            if(elect_one()){
              mbar_expect_tx(br,26624);
              bulk_load(d, SYMADDR(uint4, g_h) + (size_t)(m*NUNIT+u)*1024, 16384, br);
              bulk_load(d+16384, SYMADDR(uint4, g_wdp) + (size_t)(j*NUNIT+u)*640, 10240, br);
            }
          } else {
            if(elect_one()){ mbar_expect_tx(br,10240); tma_load_3d(d+16384,&P.tm_uld,0,m*128+(i-NUNIT)*64,j*5,br); }
          }
          __syncwarp();
          if(++slot==((isfft && i<RING5)? 5 : G2_NST)) slot=0;
        }
      }
      PROF(44);
    } else {
      DERIVE();
      if(lane==0 && warp>=10){ asm volatile("prefetch.tensormap [%0];"::"l"(warp==10? &P.tm_x : &P.tm_wg):"memory"); if(warp==11) asm volatile("prefetch.tensormap [%0];"::"l"(&P.tm_wu):"memory"); }
      if(tx_==288){
        #pragma unroll
        for(int i=18;i<38;i++) mbar_init(mb_+8*i, (i==18 || i>=30)? 2 : 1);
        asm volatile("fence.mbarrier_init.release.cluster;":::"memory");
      }
      if(tx_==320){
        #pragma unroll
        for(int i=1;i<4;i++) mbar_init(mb_+B_WFULL+8*i, 1);
        #pragma unroll
        for(int i=0;i<4;i++) mbar_init(mb_+B_WEMPTY+8*i, 1);
        asm volatile("fence.mbarrier_init.release.cluster;":::"memory");
      }
      if(tx_==352){
        #pragma unroll
        for(int i=38;i<NBAR;i++) mbar_init(mb_+8*i, (i>=43 && i<50)? 4 : (i==52? 2 : 1));
        asm volatile("fence.mbarrier_init.release.cluster;":::"memory");
      }
      __syncwarp();
      asm volatile("bar.sync 0, 384;":::"memory");
      const int tid = (int)tx_ - 288;
      if(tid==0){ *s_ready = 0; *s_epoch = atomicAdd(&g_cnt[0],1u)/NCTA + 1u; mbar_arrive(mb_+B_EPOCH); }
      if(warp==9){
        if(!extra){
          if(lane==0){ mbar_expect_tx(mb_+B_GW, 1280); bulk_load(sb+SM_GW, P.gate_w, 1280, mb_+B_GW); }
          mbar_wait(mb_+B_WFULL+24,0);
          if(lane<4){ if(b<64) pf_line((const uint8_t*)T_G128 + b*512 + lane*128); else if(b<90) pf_line((const uint8_t*)T_FFT + (b-64)*512 + lane*128); }
          #pragma unroll 1
          for(int i=1;i<nunits;i++){
            if(i==2) mbar_wait(mb_+B_GO,0);
            if(i==3) mbar_wait(mb_+B_PUBH+8,0);
            #pragma unroll 1
            for(int l=lane;l<80;l+=32) pf_weights(P.wg, P.wu, unit_of(j,i), m, l);
          }
        }
        if(isfft){
          if(!extra) mbar_wait(mb_+B_PUBV,0); else mbar_wait(mb_+B_PUBH,0);
          if(lane<4) asm volatile("prefetch.tensormap [%0];"::"l"(lane==0? &P.tm_vld : (lane==1? &P.tm_wr : (lane==2? &P.tm_wi : &P.tm_ust))):"memory");
        }
      } else if(warp==10){
        const unsigned ep1 = get_ep1();
        const unsigned* addr = (lane<28)? &g_hflag[(extra? 0 : m)*32+lane] : &g_cnt[lane==28? 128 : (lane==29? 96 : 32)];
        const unsigned target = ep1*((lane<28)? 1u : (lane==28? 192u : (lane==29? 65u : 128u)));
        const unsigned all = extra? (isfft? 0x40000000u : 0u) : (isfft? 0x77FFFFFFu : 0x37FFFFFFu);
        unsigned seen = 0; uint32_t it = 0;
        while((seen & all) != all){
          const unsigned f = ld_acquire(addr);
          const unsigned mask = __ballot_sync(0xffffffffu, (int)(f-target)>=0);
          if(mask!=seen){ seen = mask; if(lane==0) s_ready[0] = mask; }
          else __nanosleep(20);
          if(++it>(1u<<20)) TIMEOUT(3000, mask);
        }
      } else if(lane==0){
        const unsigned ep1 = get_ep1();
        if(!extra){
          mbar_wait(mb_+B_PUBV, 0);
          PROF(48);
          red_release(&g_cnt[32], 1u);
          PROF(49);
        }
        #pragma unroll 1
        for(int i=0;i<nunits;i++){
          mbar_wait(mb_+B_PUBH+8*i, 0);
          if(isfft && !extra) mbar_wait(mb_+B_PUBH+8, 0);
          if(i==1) PROF(53); if(i==3) PROF(20);
          st_release(&g_hflag[(extra? mbase+i : m)*32 + unit_of(j,i)], ep1);
          if(j<6 && i<2) red_relaxed(&g_cnt[128], 1u);
          if(i==1) PROF(54); if(i==3) PROF(21);
        }
        if(isfft){
          const int nu = extra? 1 : 2;
          #pragma unroll 1
          for(int u=0;u<nu;u++){
            mbar_wait(mb_+B_PUBU+8*u, 0);
            const int k1 = extra? 64 : (4*m + 2*(j-6) + u);
            const uint32_t sA = sb+SM_FF+u*FFT_F_BYTES;
            const bool single = (k1==0 || k1==64);
            #pragma unroll 1
            for(int ri=0; ri<(single? 1 : 2); ri++){
              tma_store_4d(&P.tm_ust, sA + ri*20480, 0,0,0, single? (k1>>6) : 2*k1+ri);
              bulk_commit();
              bulk_wait_read<0>();
            }
          }
          PROF(62);
          bulk_wait_read<0>();
          PROF(63);
          if(!extra) for(int s=5; s<G2_NST; s++){ mbar_arrive(mb_+B_G2EMPTY+8*s); mbar_arrive(mb_+B_G2EMPTY+8*s); }
          bulk_wait<0>();
          fence_async_global();
          red_relaxed(&g_cnt[96], (unsigned)nu);
          PROF(45);
        }
      }
    }
  } else {
    DERIVE();
    const int w = warp&3, g = lane>>2, tid = tx_&127;
    const long long t0 = clock64();
    auto pf_x = [&](const int idx){ pf_line(P.x + (size_t)(16*(16*j + (idx&15)) + m)*1280 + (idx>>4)*128); };
    auto pf_w = [&](const int idx){ pf_weights(P.wg, P.wu, unit_of(j,0), m, kb_perm(idx>>3, j, 8+(j>>2))*8 + (idx&7)); };
    if(wg==0 && !extra){ if(tid<16) pf_w(tid); pf_x(tid); if(tid<32) pf_x(128+tid); }

    asm volatile("bar.sync 0, 384;":::"memory");
    if(wg==0) PROF(4);
    asm volatile("setmaxnreg.inc.sync.aligned.u32 232;");
    if(wg==0 && !extra){
      while(clock64()-t0 < 600);
      if(tid<64) pf_w(16+tid);
    }
    auto gate_rows = [&](){
      mbar_wait(mb_+B_GW,0);
      const int row = 16*j + 4*w + (lane>>3), ch = lane&7;
      const uint32_t xa = sb + SM_X + row*128 + ((ch^(row&7))<<4), ga = sb + SM_GW + ch*16;
      float s0 = 0.f, s1 = 0.f;
      #pragma unroll
      for(int kb=0;kb<10;kb++){
        const uint4 xv = lds128(xa + kb*16384), gw = lds128(ga + kb*128);
        s0 += bf_lo(xv.x)*bf_lo(gw.x) + bf_lo(xv.y)*bf_lo(gw.y) + bf_lo(xv.z)*bf_lo(gw.z) + bf_lo(xv.w)*bf_lo(gw.w);
        s1 += bf_hi(xv.x)*bf_hi(gw.x) + bf_hi(xv.y)*bf_hi(gw.y) + bf_hi(xv.z)*bf_hi(gw.z) + bf_hi(xv.w)*bf_hi(gw.w);
      }
      s0 += s1;
      s0 += __shfl_xor_sync(0xffffffffu, s0, 1); s0 += __shfl_xor_sync(0xffffffffu, s0, 2); s0 += __shfl_xor_sync(0xffffffffu, s0, 4);
      if(ch==0) g_gate[m*128 + row] = 1.f/(1.f+__expf(-s0));
    };
    if(wg==1 && !extra){
      const int t = lane&3, box2 = 8 + (j>>2);
      uint4 A[2][8];
      #pragma unroll
      for(int mh=0;mh<2;mh++){
        #pragma unroll
        for(int s=0;s<8;s++) A[mh][s] = ldg_nc((const uint4*)T_F128 + ((mh*4+w)*8+s)*32 + lane);
      }
      float acc[2][32], acb[2][8];
      mbar_wait(mb_+B_XFULL+8*j,0);
      PROF(50);
      const uint32_t dB = desc_lo(sb+SM_X+j*16384, 0), dB2 = desc_lo(sb+SM_X+box2*16384+(j&3)*32, 0);
      wg_fence();
      #pragma unroll
      for(int mh=0;mh<2;mh++){
        #pragma unroll
        for(int s=0;s<8;s++) wgmma_rs_n64<1>(acc[mh], A[mh][s].x,A[mh][s].y,A[mh][s].z,A[mh][s].w, mk_desc<1024>(dB + s*128), s>0);
      }
      wg_commit(); wg_wait<0>(); fence_regs(acc[0]); fence_regs(acc[1]);
      PROF(52);
      uint8_t* vp = (uint8_t*)g_V + (size_t)(16*w + g)*20480 + m*1280;
      #pragma unroll
      for(int mh=0;mh<2;mh++){
        #pragma unroll
        for(int q=0;q<2;q++){
          #pragma unroll
          for(int hf=0;hf<2;hf++){
            uint32_t a4[4];
            #pragma unroll
            for(int i=0;i<4;i++) a4[i] = pack_bf16(acc[mh][4*(4*q+i)+2*hf], acc[mh][4*(4*q+i)+2*hf+1]);
            stg128(vp + mh*1310720 + j*128 + t*16 + q*64 + hf*163840, quad_transpose(a4[0],a4[1],a4[2],a4[3],t));
          }
        }
      }
      mbar_wait(mb_+B_XFULL+8*box2,0);
      wg_fence();
      #pragma unroll
      for(int mh=0;mh<2;mh++){
        #pragma unroll
        for(int s=0;s<8;s++) wgmma_rs_n16<1>(acb[mh], A[mh][s].x,A[mh][s].y,A[mh][s].z,A[mh][s].w, mk_desc<1024>(dB2 + s*128), s>0);
      }
      wg_commit(); wg_wait<0>(); fence_regs(acb[0]); fence_regs(acb[1]);
      #pragma unroll
      for(int mh=0;mh<2;mh++){
        const uint4 v = quad_transpose(pack_bf16(acb[mh][0],acb[mh][1]), pack_bf16(acb[mh][4],acb[mh][5]), pack_bf16(acb[mh][2],acb[mh][3]), pack_bf16(acb[mh][6],acb[mh][7]), t);
        stg128(vp + mh*1310720 + (t>>1)*163840 + box2*128 + (j&3)*32 + (t&1)*16, v);
      }
      __syncwarp();
      mbar_arrive_if(mb_+B_PUBV, lane==0);
      PROF(10);
      if(isfft){
        #pragma unroll 1
        for(int kb=0;kb<10;kb++) mbar_wait(mb_+B_XFULL+8*kb,0);
        gate_rows();
        __syncwarp();
        mbar_arrive_if(mb_+B_PUBH+8, lane==0);
        named_bar(2,128);
        if(tid==0){ mbar_arrive(mb_+B_VFREE); mbar_arrive(mb_+B_XFREE); }
        PROF(46);
      }
    }
    for(int i=wg;i<nunits;i+=2){
      float acc[2][64];
      int cnt = i*10; int slot = cnt&(W_NST-1), ph = (cnt/W_NST)&1; int prev=-1;
      const bool prog = !extra && (i==3) && tid==0;
      const int k0 = extra? 0 : j, k1 = extra? 1 : 8+(j>>2);
      auto kblock = [&](const int p, auto first){
        const int kb = (i==0)? kb_perm(p, k0, k1) : p;
        mbar_wait(i==0? mb_+B_XFULL+8*kb : mb_+B_TURN, i==0? 0 : (i+1)&1);
        mbar_wait(mb_+B_WFULL+8*slot, ph);
        const uint32_t res = sb+SM_X+kb*16384, rng = sb+SM_W+slot*16384;
        const uint32_t dA = desc_lo(extra? rng : res, 16), dB = desc_lo(extra? res : rng, 8192);
        wg_fence();
        #pragma unroll
        for(int kk=0;kk<4;kk++){
          #pragma unroll
          for(int mh=0;mh<2;mh++) wgmma_ss_n128<0,1>(acc[mh], mk_desc<1024>(dA + mh*512 + kk*2), mk_desc<1024>(dB + kk*128), (decltype(first)::value && kk==0)? 0 : 1);
        }
        wg_commit();
        mbar_arrive_if(mb_+B_TURN, p==9 && tid==0);
        mbar_arrive_if(mb_+B_GO, p==9 && tid==0 && i==0);
        wg_wait<1>();
        mbar_arrive_if(mb_+B_WEMPTY+8*prev, prev>=0 && tid==0);
        const int srel = (int)((0x4F3F21F0FFull >> (4*p)) & 15);
        mbar_arrive_if(mb_+B_G2EMPTY+8*(srel&7), prog && srel!=15);
        mbar_arrive_if(mb_+B_VFREE, isfft && !extra && p==7 && tid==0);
        prev=slot;
        if(++slot==W_NST){slot=0; ph^=1;}
      };
      kblock(0, TrueT{});
      #pragma unroll 1
      for(int kb=1;kb<10;kb++) kblock(kb, FalseT{});
      wg_wait<0>(); fence_regs(acc[0]); fence_regs(acc[1]);
      if(tid==0){
        mbar_arrive(mb_+B_WEMPTY+8*prev);

        if(!extra && i==3) for(int s=5; s<G2_NST; s++) mbar_arrive(mb_+B_G2EMPTY+8*s);

        if(isfft && i+2>=nunits) mbar_arrive(mb_+B_XFREE);
      }
      if(i<4) PROF(12+2*i);
      const int u = unit_of(j,i);
      auto h_epilogue = [&](){
        uint8_t* hp = (uint8_t*)g_h + (size_t)((extra? mbase+i : m)*NUNIT+u)*16384 + (2*w)*1024 + (lane&3)*128 + g*16;
        #pragma unroll
        for(int mh=0;mh<2;mh++){
          #pragma unroll
          for(int q=0;q<2;q++){
            #pragma unroll
            for(int hf=0;hf<2;hf++){
              uint32_t a4[4];
              #pragma unroll
              for(int ii=0;ii<4;ii++){ const int jn=4*q+ii;
                a4[ii] = pack_bf16(fmaxf(acc[mh][4*jn+2*hf],0.f)*acc[mh][32+4*jn+2*hf], fmaxf(acc[mh][4*jn+2*hf+1],0.f)*acc[mh][32+4*jn+2*hf+1]); }
              stg128(hp + mh*8192 + hf*1024 + q*512, make_uint4(a4[0],a4[1],a4[2],a4[3]));
            }
          }
        }
      };
      if(j<6 && i<2){
        auto wd_item = [&](const int l, const int e, uint32_t& src, uint32_t& dst){
          const int gq = (m*6+j)*45 + 4*i + w + 8*e;
          const int item = gq/5, sub = gq - item*5, img = item>>2, jj = img/27, uu = img - jj*27;
          const int rg = 2*(item&3) + (l>>4), kr = ((l>>1)&7), nc = 2*sub + (l&1);
          src = (uint32_t)((uu*64 + 32*(rg>>2) + 8*(kr>>1) + 2*(rg&3) + (kr&1))*1280 + jj*160 + nc*16);
          dst = (uint32_t)(img*10240 + nc*1024 + rg*128 + kr*16);
        };
        int l1 = lane; asm volatile("mov.u32 %0, %0;":"+r"(l1)::"memory");
        uint4 v[6];
        #pragma unroll
        for(int e=0;e<6;e++){
          uint32_t src, dst; wd_item(l1, e, src, dst);
          if(4*i+w+8*e<45) v[e] = ldg_nc((const uint4*)(P.wd + src));
        }
        PROF(61);
        h_epilogue();
        PROF(59);
        int l2 = lane; asm volatile("mov.u32 %0, %0;":"+r"(l2)::"memory");
        #pragma unroll
        for(int e=0;e<6;e++){
          uint32_t src, dst; wd_item(l2, e, src, dst);
          if(4*i+w+8*e<45) stg128((uint8_t*)g_wdp + dst, v[e]);
        }
      } else h_epilogue();
      if(!extra && i==2){
        gate_rows();
        named_bar(1,128);
        if(tid==0) for(int s=0; s<G2_NST; s++) mbar_arrive(mb_+B_G2EMPTY+8*s);
        PROF(46);
      }
      __syncwarp();
      mbar_arrive_if(mb_+B_PUBH+8*i, lane==0);
      if(i<4) PROF(13+2*i);
    }
    if(isfft && (!extra || wg==0)){
      const int k1 = extra? 64 : (4*m + 2*(j-6) + wg);
      mbar_wait(mb_+B_XFREE,0);
      PROF(22+wg);
      fft_unit(sb+SM_FF+wg*FFT_F_BYTES, sb+SM_FA+wg*FFT_A_BYTES, sb+SM_FT, sb+SM_FP+wg*FFT_PARK, mb_+B_VFULL+8*wg, mb_+B_FFULL+8*wg, SM_MISC+B_TAB-SM_FT, SM_MISC+B_G2EMPTY-SM_FT, k1, 1+wg,
               nullptr);
    }
    {
    DERIVE();
    const int wg = __shfl_sync(0xffffffffu, (int)tx_>>7, 0), w = __shfl_sync(0xffffffffu, ((int)tx_>>5)&3, 0);
    const int g = lane>>2, tid = tx_&127, tile = lane>>3, r8 = lane&7;
    if(isfft && (!extra || wg==0)){
      if(tid==0){
        if(!extra) for(int s=2; s<5; s++) mbar_arrive(mb_+B_G2EMPTY+8*s);
      }
      mbar_arrive_if(mb_+B_PUBU+8*wg, lane==0);
      PROF(24+wg);
    }
    if(!extra){
      float acc1[40], acc2[40];
      int slot=0, prev=-1; uint32_t phm=0;
      uint4 A[8];
      #pragma unroll
      for(int s=0;s<8;s++) A[s] = ldg_nc((const uint4*)T_G128 + ((wg*4+w)*8+s)*32 + lane);
      auto g2block = [&](const int i, auto first){
        mbar_wait(mb_+B_G2FULL+8*slot, (phm>>slot)&1);
        phm ^= 1u<<slot;
        const uint32_t st = sb + slot*G2_STAGE;
        const uint32_t dA = desc_lo(st+wg*8192, 128), dB = desc_lo(st+16384, 128);
        wg_fence();
        #pragma unroll
        for(int kk=0;kk<4;kk++) wgmma_ss_n80<0,1>(acc1, mk_desc<1024,0>(dA+kk*16), mk_desc<1024,0>(dB+kk*16), (decltype(first)::value && kk==0)? 0 : 1);
        wg_commit();
        wg_wait<1>();
        mbar_arrive_if(mb_+B_G2EMPTY+8*prev, prev>=0 && tid==0);
        prev=slot;
        if(++slot==((isfft && i<RING5)? 5 : G2_NST)) slot=0;
      };
      g2block(0, TrueT{});
      #pragma unroll 1
      for(int i=1;i<=21;i++) g2block(i, FalseT{});
      const int row0 = 64*wg + 16*w + g;
      float g0, g1;
      asm volatile("ld.relaxed.gpu.global.f32 %0, [%1];":"=f"(g0):"l"(g_gate+m*128+row0));
      asm volatile("ld.relaxed.gpu.global.f32 %0, [%1];":"=f"(g1):"l"(g_gate+m*128+row0+8));
      #pragma unroll 1
      for(int i=22;i<NUNIT;i++) g2block(i, FalseT{});
      PROF(28+wg);
      #pragma unroll
      for(int hb=0;hb<2;hb++){
        mbar_wait(mb_+B_G2FULL+8*slot, (phm>>slot)&1);
        const uint32_t dB = desc_lo(sb + slot*G2_STAGE + 16384, 2048);
        wg_fence();
        #pragma unroll
        for(int kk=0;kk<4;kk++){ const uint4 a=A[4*hb+kk]; wgmma_rs_n80<1>(acc2, a.x,a.y,a.z,a.w, mk_desc<256,3>(dB+kk*32), (hb|kk)!=0); }
        wg_commit();
        if(++slot==G2_NST) slot=0;
      }
      wg_wait<0>(); fence_regs(acc1); fence_regs(acc2);
      PROF(30+wg);
      named_bar(4,256);
      const uint32_t rb = sb + (64*wg + 16*w + 8*(tile&1) + r8)*160 + (tile>>1)*16;
      #pragma unroll
      for(int jj=0;jj<5;jj++){
        uint32_t q[4];
        #pragma unroll
        for(int hh=0;hh<2;hh++){
          const int jn=2*jj+hh;
          q[2*hh]   = pack_bf16(fmaf(g0, acc2[4*jn]  -acc1[4*jn],   acc1[4*jn]),   fmaf(g0, acc2[4*jn+1]-acc1[4*jn+1], acc1[4*jn+1]));
          q[2*hh+1] = pack_bf16(fmaf(g1, acc2[4*jn+2]-acc1[4*jn+2], acc1[4*jn+2]), fmaf(g1, acc2[4*jn+3]-acc1[4*jn+3], acc1[4*jn+3]));
        }
        stmatrix_x4(rb + jj*32, q[0],q[1],q[2],q[3]);
      }
      fence_async_smem();
      named_bar(1+wg,128);
      if(tid==0){
        tma_store_3d(&P.tm_out, sb + 64*wg*160, j*80, m, 64*wg);
        bulk_commit(); bulk_wait_read<0>();
      }
      PROF(32+wg);
    }
    }
  }
}

typedef CUresult (*EncFn)(CUtensorMap*, CUtensorMapDataType, cuuint32_t, void*, const cuuint64_t*, const cuuint64_t*, const cuuint32_t*, const cuuint32_t*, CUtensorMapInterleave, CUtensorMapSwizzle, CUtensorMapL2promotion, CUtensorMapFloatOOBfill);

static void enc_map(EncFn enc, CUtensorMap* tm, const void* base, int rank, const cuuint64_t* gd, const cuuint64_t* gs, const cuuint32_t* bx, CUtensorMapSwizzle sw){
  cuuint32_t es[5]={1,1,1,1,1};
  CUresult r = enc(tm, CU_TENSOR_MAP_DATA_TYPE_BFLOAT16, rank, (void*)base, gd, gs, bx, es, CU_TENSOR_MAP_INTERLEAVE_NONE, sw, CU_TENSOR_MAP_L2_PROMOTION_L2_256B, CU_TENSOR_MAP_FLOAT_OOB_FILL_NONE);
  (void)r;
}

extern "C" void kernel_launch(void* const* d_in, const int* in_sizes, int n_in, void* d_out, int out_size){
  static EncFn enc = nullptr;
  static void *pV=nullptr, *pU=nullptr;
  if(!enc){
    void* fn=nullptr; cudaDriverEntryPointQueryResult q;
    cudaGetDriverEntryPoint("cuTensorMapEncodeTiled",&fn,cudaEnableDefault,&q); enc=(EncFn)fn;
    cudaFuncSetAttribute(gated_mix_kernel, cudaFuncAttributeMaxDynamicSharedMemorySize, SM_TOTAL);
    cudaGetSymbolAddress(&pV, g_V); cudaGetSymbolAddress(&pU, g_U);
  }
  Params P;
  { cuuint64_t gd[3]={640,16,128}, gs[2]={1280,20480}; cuuint32_t bx[3]={64,1,128};
    enc_map(enc,&P.tm_x,d_in[0],3,gd,gs,bx,CU_TENSOR_MAP_SWIZZLE_128B);
    cuuint32_t bo[3]={80,1,64};
    enc_map(enc,&P.tm_out,d_out,3,gd,gs,bo,CU_TENSOR_MAP_SWIZZLE_NONE); }
  { cuuint64_t gd[2]={1728,640}, gs[1]={3456}; cuuint32_t bx[2]={64,64};
    enc_map(enc,&P.tm_wg,d_in[4],2,gd,gs,bx,CU_TENSOR_MAP_SWIZZLE_128B);
    enc_map(enc,&P.tm_wu,d_in[5],2,gd,gs,bx,CU_TENSOR_MAP_SWIZZLE_128B); }
  { cuuint64_t gd[4]={64,16,10,128}; cuuint32_t bx[4]={64,16,10,1};
    cuuint64_t gsv[3]={1280,128,20480}; enc_map(enc,&P.tm_vld,pV,4,gd,gsv,bx,CU_TENSOR_MAP_SWIZZLE_128B);
    cuuint64_t gsu[3]={163840,128,1280}; enc_map(enc,&P.tm_ust,pU,4,gd,gsu,bx,CU_TENSOR_MAP_SWIZZLE_128B); }
  { cuuint64_t gd[3]={16,2048,40}, gs[2]={1280,32}; cuuint32_t bx[3]={16,64,5};
    enc_map(enc,&P.tm_uld,pU,3,gd,gs,bx,CU_TENSOR_MAP_SWIZZLE_32B); }
  { cuuint64_t gd[2]={41088,16}, gs[1]={82176}; cuuint32_t bx[2]={168,16};
    enc_map(enc,&P.tm_wr,d_in[1],2,gd,gs,bx,CU_TENSOR_MAP_SWIZZLE_NONE);
    enc_map(enc,&P.tm_wi,d_in[2],2,gd,gs,bx,CU_TENSOR_MAP_SWIZZLE_NONE); }
  P.x=(const uint8_t*)d_in[0]; P.wg=(const uint8_t*)d_in[4]; P.wu=(const uint8_t*)d_in[5];
  P.wr=(const uint8_t*)d_in[1]; P.wi=(const uint8_t*)d_in[2]; P.wd=(const uint8_t*)d_in[6]; P.gate_w=(const uint16_t*)d_in[7];
  P.prof=nullptr;
  gated_mix_kernel<<<132,384,SM_TOTAL,cudaStreamPerThread>>>(P);
}
```
